```python
import torch

def _softmax(x, axis=-1):
    return torch.softmax(x, dim=axis)
def _gelu(x):
    return torch.nn.functional.gelu(x, approximate="tanh")
def _silu(x):
    return torch.nn.functional.silu(x)
def _sigmoid(x):
    return torch.sigmoid(x)
def _layernorm(x, axis=-1, eps=1e-5):
    m = x.mean(dim=axis, keepdim=True)
    v = x.var(dim=axis, keepdim=True, unbiased=False)
    return (x - m) / torch.sqrt(v + eps)
def _scatter_add(tgt, idx, src, axis=0):
    return tgt.clone().index_add_(axis, idx, src)
def _segment_sum(src, seg, n):
    out = torch.zeros((n,) + src.shape[1:], dtype=src.dtype)
    return out.index_add_(0, seg, src)
def _pad(x, pw):
    flat = tuple(v for pair in reversed(pw) for v in pair)
    return torch.nn.functional.pad(x, flat)

kernel_name = 'standalone__molecular_angular_gemnet__graph'

def setup_inputs():

    _w = (lambda a: (lambda t: t.to(torch.bfloat16) if t.is_floating_point() else t)(torch.as_tensor(a)))
    N, deg, De, L = 12500, 64, 4, 1
    E = N * deg
    T = E * deg
    NR = 8
    dist = torch.rand(E).to(float)
    angle = (torch.rand(T) * torch.pi).to(float)
    centers = torch.linspace(0.0, 1.0, NR).to(float)
    ang_freq = torch.arange(1, L + 1).to(float)
    return {
        "m": _w((lambda *s: torch.randn(*s, dtype=torch.bfloat16) * 0.05)(E, De)),
        "idx_in": _w((lambda lo, hi, *s: torch.randint(lo, hi, s))(0, E, T).to(torch.int64)),
        "idx_out": _w((lambda lo, hi, *s: torch.randint(lo, hi, s))(0, E, T).to(torch.int64)),
        "dist": _w(dist),
        "angle": _w(angle),
        "centers": _w(centers),
        "ang_freq": _w(ang_freq),
        "w_rbf": _w((lambda *s: torch.randn(*s, dtype=torch.bfloat16) * 0.2)(NR, De)),
        "w_sbf": _w((lambda *s: torch.randn(*s, dtype=torch.bfloat16) * 0.2)(NR * L, De)),
        "w_down": _w((lambda *s: torch.randn(*s, dtype=torch.bfloat16) * 0.2)(De, De)),
        "w_up": _w((lambda *s: torch.randn(*s, dtype=torch.bfloat16) * 0.2)(De, De)),
    }

def reference(m, idx_in, idx_out, dist, angle, centers, ang_freq, w_rbf, w_sbf, w_down, w_up):
    E, De = m.shape[0], m.shape[1]
    NR = centers.shape[0]
    L = ang_freq.shape[0]
    rbf = torch.exp(-10.0 * (dist[:, None] - centers[None, :]) ** 2)
    cbf = torch.cos(ang_freq[None, :] * angle[:, None])
    rbf_t = rbf[idx_out]
    sbf = torch.reshape(rbf_t[:, :, None] * cbf[:, None, :], (-1, NR * L))
    x = (m[idx_in] @ w_down) * (sbf @ w_sbf)
    agg = _segment_sum(x, idx_out, E)
    return m + (agg @ w_up) * (rbf @ w_rbf)
```

```cpp
#include <cuda_runtime.h>
#include <cuda_bf16.h>
#include <stdint.h>

constexpr int MAX_E = 1 << 20;
__device__ float4 g_acc[MAX_E];

__device__ __forceinline__ float bf_lo(uint32_t v) { return __uint_as_float(v << 16); }
__device__ __forceinline__ float bf_hi(uint32_t v) { return __uint_as_float(v & 0xffff0000u); }
__device__ __forceinline__ float rbf16(float x) { return __bfloat162float(__float2bfloat16_rn(x)); }

__global__ void zero_kernel(int E) {
    int e = blockIdx.x * blockDim.x + threadIdx.x;
    if (e < E) g_acc[e] = make_float4(0.f, 0.f, 0.f, 0.f);
}

__global__ void __launch_bounds__(256) direct_kernel(const uint2* __restrict__ m, const int* __restrict__ idx_in,
                                                     const int* __restrict__ idx_out,
                                                     const __nv_bfloat16* __restrict__ angle,
                                                     const __nv_bfloat16* __restrict__ freq, int T) {
    float f = __bfloat162float(freq[0]);
    for (int t = blockIdx.x * blockDim.x + threadIdx.x; t < T; t += gridDim.x * blockDim.x) {
        uint2 v = __ldg(m + idx_in[t]);
        float c = rbf16(cosf(rbf16(f * __bfloat162float(angle[t]))));
        asm volatile("red.global.add.v4.f32 [%0], {%1,%2,%3,%4};" ::"l"(g_acc + idx_out[t]), "f"(c * bf_lo(v.x)),
                     "f"(c * bf_hi(v.x)), "f"(c * bf_lo(v.y)), "f"(c * bf_hi(v.y))
                     : "memory");
    }
}

__global__ void __launch_bounds__(256) epilogue_kernel(const uint2* __restrict__ m, const __nv_bfloat16* __restrict__ dist,
                                                       const __nv_bfloat16* __restrict__ centers,
                                                       const __nv_bfloat16* __restrict__ w_rbf,
                                                       const __nv_bfloat16* __restrict__ w_sbf,
                                                       const __nv_bfloat16* __restrict__ w_down,
                                                       const __nv_bfloat16* __restrict__ w_up, uint2* __restrict__ out,
                                                       int E) {
    __shared__ float w[8 + 32 + 32 + 16 + 16];
    int tid = threadIdx.x;
    if (tid < 8) w[tid] = __bfloat162float(centers[tid]);
    else if (tid < 40) w[tid] = __bfloat162float(w_rbf[tid - 8]);
    else if (tid < 72) w[tid] = __bfloat162float(w_sbf[tid - 40]);
    else if (tid < 88) w[tid] = __bfloat162float(w_down[tid - 72]);
    else if (tid < 104) w[tid] = __bfloat162float(w_up[tid - 88]);
    __syncthreads();
    int e = blockIdx.x * blockDim.x + tid;
    if (e >= E) return;
    float d = __bfloat162float(dist[e]);
    float g[4] = {0, 0, 0, 0}, s[4] = {0, 0, 0, 0};
#pragma unroll
    for (int r = 0; r < 8; r++) {
        float x = rbf16(d - w[r]);
        float b = rbf16(expf(rbf16(-10.0f * rbf16(x * x))));
#pragma unroll
        for (int j = 0; j < 4; j++) {
            g[j] = fmaf(b, w[8 + r * 4 + j], g[j]);
            s[j] = fmaf(b, w[40 + r * 4 + j], s[j]);
        }
    }
    float4 a4 = g_acc[e];
    float a[4] = {a4.x, a4.y, a4.z, a4.w}, agg[4];
#pragma unroll
    for (int j = 0; j < 4; j++) {
        float t = 0.f;
#pragma unroll
        for (int k = 0; k < 4; k++) t = fmaf(a[k], w[72 + k * 4 + j], t);
        agg[j] = rbf16(t * s[j]);
    }
    uint2 mv = m[e];
    float mm[4] = {bf_lo(mv.x), bf_hi(mv.x), bf_lo(mv.y), bf_hi(mv.y)}, o[4];
#pragma unroll
    for (int j = 0; j < 4; j++) {
        float t = 0.f;
#pragma unroll
        for (int k = 0; k < 4; k++) t = fmaf(agg[k], w[88 + k * 4 + j], t);
        o[j] = mm[j] + rbf16(rbf16(t) * rbf16(g[j]));
    }
    __nv_bfloat162 p0 = __floats2bfloat162_rn(o[0], o[1]), p1 = __floats2bfloat162_rn(o[2], o[3]);
    out[e] = make_uint2(*(uint32_t*)&p0, *(uint32_t*)&p1);
}

extern "C" void kernel_launch(void* const* d_in, const int* in_sizes, int n_in, void* d_out, int out_size) {
    const uint2* m = (const uint2*)d_in[0];
    const int* idx_in = (const int*)d_in[1];
    const int* idx_out = (const int*)d_in[2];
    const __nv_bfloat16* dist = (const __nv_bfloat16*)d_in[3];
    const __nv_bfloat16* angle = (const __nv_bfloat16*)d_in[4];
    int E = in_sizes[3], T = in_sizes[1];
    zero_kernel<<<(E + 255) / 256, 256>>>(E);
    direct_kernel<<<132 * 8, 256>>>(m, idx_in, idx_out, angle, (const __nv_bfloat16*)d_in[6], T);
    epilogue_kernel<<<(E + 255) / 256, 256>>>(m, dist, (const __nv_bfloat16*)d_in[5], (const __nv_bfloat16*)d_in[7],
                                              (const __nv_bfloat16*)d_in[8], (const __nv_bfloat16*)d_in[9],
                                              (const __nv_bfloat16*)d_in[10], (uint2*)d_out, E);
}
```

```cpp
#include <cuda_runtime.h>
#include <cuda_bf16.h>
#include <stdint.h>


typedef unsigned long long u64;
constexpr uint32_t magic_of(uint32_t d) { return (uint32_t)(((1ull << 32) + d - 1) / d); }
constexpr uint32_t slice_of(uint32_t total, uint32_t n) {
    uint32_t d = ((total + n - 1) / n + 1) & ~1u;
    while (!((uint64_t)(n * d - 1) * magic_of(d) < ((uint64_t)n << 32))) d += 2;
    return d;
}
constexpr int E_CAP = 800000;
constexpr int NI = 32, NO = 28, NG = 2, IG = NI / NG;
constexpr uint32_t SI = slice_of(E_CAP, NI), SO = slice_of(E_CAP, NO);
constexpr uint32_t MI = magic_of(SI), MO = magic_of(SO);
constexpr int C = 16, NP = 5, GB = NO * IG;
constexpr int NW = 27, ITERS = 2, STEP = NW * ITERS * 128;
constexpr int KA = 132, KV = 88;
constexpr int N2 = NI, N3 = NO * NG;
constexpr int ASEG = NO * C * 4, XSEG = IG * C * 2, VSEG = IG * C * 8;
constexpr int AG = IG * ASEG, XG = NO * XSEG, AXG = AG + XG + GB, VG = NO * VSEG;
constexpr int PA = (AXG + 4095) / 4096, PV = (VG + 4095) / 4096;
static_assert(AG % 4096 == 0 && AG == 2 * XG && (AG + XG) / 4096 == (AXG - 1) / 4096 && NO % 4 == 0 && IG == 16, "layout");
static_assert(PA <= 16 && PV <= 16 && KA >= 32 && KV >= 32 && KA + KV < 256, "ring");
constexpr int MAX_UNITS = 4096;
constexpr int NR = 2, LOGCAP = 8192, MAX_N1 = 56;
static_assert(NR % 2 == 0 && NR >= 2 && NR * ITERS * 128 <= LOGCAP, "log");
constexpr int NCH = NW * NR * ITERS * 4;
constexpr int SM_CNT = 0, SM_CB = NG * GB * 4, SM_LC = SM_CB + 2 * GB, SM_X = SM_LC + 256,
              SM_A = SM_X + NP * XG, SM_CH = SM_A + NP * AG, SM_S1_END = SM_CH + NCH * 4 + 128;
constexpr int MAX_CTA = 144;
constexpr int SM_AUX = SO * 8;
constexpr int AUX_TAB = 0, AUX_CLS = 1536, AUX_INFO = AUX_CLS + MAX_CTA * 4, AUX_MISC = AUX_INFO + MAX_CTA * 2, AUX_PUB = AUX_MISC + 32,
              AUX_DUMMY = AUX_PUB + 128, AUX_W = AUX_DUMMY + 256, AUX_END = AUX_W + 416;
constexpr int SMEM_BYTES = SM_AUX + AUX_END;
static_assert(SM_S1_END <= SM_AUX && SI * 8 <= SM_AUX && SMEM_BYTES <= 232448 && SM_X % 128 == 0 && KA * 8 + KV * 4 <= AUX_CLS && AUX_W % 16 == 0, "smem");

constexpr int PFL = 3 * MAX_UNITS * 4 / 4096, NSL = KA + KV + 1;
__device__ __align__(8192) unsigned char g_ring[(size_t)(KA * PA + KV * PV + PFL) * 8192];
__device__ __align__(8192) unsigned char g_probe[8192];
__device__ uint2 g_info[MAX_CTA];
__device__ uint32_t g_sync[96];
__device__ uint2 g_log[MAX_N1 * NW * LOGCAP];
__device__ uint2 g_agg[NO * SO];
constexpr int FL_READY = 0, FL_S2 = 1, FL_S3 = 2;

__device__ __forceinline__ float bf_lo(uint32_t v) { return __uint_as_float(v << 16); }
__device__ __forceinline__ float bf_hi(uint32_t v) { return __uint_as_float(v & 0xffff0000u); }
__device__ __forceinline__ float rbf16(float x) { return __bfloat162float(__float2bfloat16_rn(x)); }
__device__ __forceinline__ uint32_t hmul2(uint32_t a, uint32_t b) {
    uint32_t d; asm("mul.rn.bf16x2 %0,%1,%2;" : "=r"(d) : "r"(a), "r"(b)); return d;
}
__device__ __forceinline__ uint32_t hadd2(uint32_t a, uint32_t b) {
    uint32_t d; asm("add.rn.bf16x2 %0,%1,%2;" : "=r"(d) : "r"(a), "r"(b)); return d;
}
__device__ __forceinline__ uint32_t dup_bf16(float x) {
    uint32_t d; asm("cvt.rn.bf16x2.f32 %0,%1,%1;" : "=r"(d) : "f"(x)); return d;
}
__device__ __forceinline__ uint32_t pack2(float lo, float hi) {
    uint32_t d; asm("cvt.rn.bf16x2.f32 %0,%2,%1;" : "=r"(d) : "f"(lo), "f"(hi)); return d;
}
__device__ __noinline__ float cos_slow(float x) { return cosf(x); }
__device__ __forceinline__ float cos_any(float x) { return fabsf(x) < 32.f ? __cosf(x) : cos_slow(x); }
__device__ __forceinline__ void bar_sync(int id, int n) { asm volatile("barrier.sync.aligned %0,%1;" ::"r"(id), "r"(n) : "memory"); }
__device__ __forceinline__ void bar_arrive(int id, int n) { asm volatile("barrier.arrive.aligned %0,%1;" ::"r"(id), "r"(n) : "memory"); }
__device__ __forceinline__ uint32_t ld_acquire(const uint32_t* p) {
    uint32_t v; asm volatile("ld.acquire.gpu.global.u32 %0,[%1];" : "=r"(v) : "l"(p) : "memory"); return v;
}
__device__ __forceinline__ uint32_t ld_relaxed(const uint32_t* p) {
    uint32_t v; asm volatile("ld.relaxed.gpu.global.u32 %0,[%1];" : "=r"(v) : "l"(p) : "memory"); return v;
}
__device__ __forceinline__ void st128(void* p, uint4 v) {
    asm volatile("{.reg .b64 a,b; .reg .b128 q; mov.b64 a,{%1,%2}; mov.b64 b,{%3,%4}; mov.b128 q,{a,b}; st.relaxed.gpu.global.b128 [%0],q;}" ::"l"(p), "r"(v.x), "r"(v.y), "r"(v.z), "r"(v.w) : "memory");
}
__device__ __forceinline__ uint4 ld128(const void* p) {
    uint4 v;
    asm volatile("{.reg .b64 a,b; .reg .b128 q; ld.relaxed.gpu.global.b128 q,[%4]; mov.b128 {a,b},q; mov.b64 {%0,%1},a; mov.b64 {%2,%3},b;}" : "=r"(v.x), "=r"(v.y), "=r"(v.z), "=r"(v.w) : "l"(p) : "memory");
    return v;
}
__device__ __forceinline__ void wait_flag(const uint32_t* p, uint32_t want) {
    int spins = 0;
    while (ld_relaxed(p) < want) {
        __nanosleep(50);
        if (++spins > (1 << 22)) __trap();
    }
}
__device__ __forceinline__ uint32_t slot_a(int s) { return s * (PA * 8192); }
__device__ __forceinline__ uint32_t slot_v(int s) { return KA * PA * 8192 + s * (PV * 8192); }
__device__ __forceinline__ uint32_t ring_off(uint32_t clsg, uint32_t off) {
    return ((off >> 12) << 13) + (((clsg >> (off >> 12)) & 1) << 12) + (off & 4095);
}
__device__ __forceinline__ uint32_t cls_of(const unsigned char* sm, int s, int g) {
    return ((const uint16_t*)(sm + SM_AUX + AUX_CLS))[s] ^ (g ? ~0u : 0u);
}
__device__ __forceinline__ uint32_t* flag_ptr(uint32_t clsf, int type, int u) {
    return (uint32_t*)(g_ring + slot_v(KV) + ring_off(clsf, (type * MAX_UNITS + u) * 4));
}
__device__ __forceinline__ bool elect_one() {
    uint32_t r; asm volatile("{.reg .pred p; elect.sync _|p,0xffffffff; selp.u32 %0,1,0,p;}" : "=r"(r)); return r;
}
template <int NCW, class F>
__device__ __forceinline__ void poller(uint32_t clsf, uint32_t want1, int type2, int lag2, uint32_t want2, int units, uint32_t pub, int hook_at, F hook) {
    const int lane = threadIdx.x & 31;
    int u = lane < NCW ? lane : units, spins = 0;
    while (__any_sync(0xffffffffu, u < units)) {
        if (__shfl_sync(0xffffffffu, u, 0) >= hook_at) { hook(); hook_at = 0x7fffffff; }
        const int uc = min(u, units - 1);
        const uint32_t v1 = ld_relaxed(flag_ptr(clsf, FL_READY, uc));
        const uint32_t v2 = ld_relaxed(flag_ptr(clsf, type2, max(uc - lag2, 0)));
        const bool hit = u < units && v1 >= want1 && (v2 >= want2 || u < lag2);
        if (__any_sync(0xffffffffu, hit)) {
            asm volatile("fence.acquire.gpu;" ::: "memory");
            if (hit) u += NCW;
            asm volatile("st.release.cta.shared.u32 [%0],%1;" ::"r"(pub + lane * 4), "r"(u) : "memory");
            spins = 0;
        } else if (++spins > (1 << 22)) __trap();
    }
}
__device__ __forceinline__ void wait_pub(uint32_t addr, int u) {
    while (true) {
        int v; asm volatile("ld.acquire.cta.shared.u32 %0,[%1];" : "=r"(v) : "r"(addr) : "memory");
        if (v > u) break;
        __nanosleep(40);
    }
}
__device__ __forceinline__ int upper_is_near(unsigned char* q) {
    ((uint4*)q)[0] = ((uint4*)q)[1] = ((uint4*)(q + 4096))[0] = ((uint4*)(q + 4096))[1] = make_uint4(0, 0, 0, 0);
    uint32_t best[2] = {~0u, ~0u};
#pragma unroll
    for (int r = 0; r < 2 * 2; r++) {
        uint32_t t0, t1, v;
        asm volatile("mov.u32 %0,%%clock;" : "=r"(t0)::"memory");
        asm volatile("atom.global.exch.b32 %0,[%1],0;" : "=r"(v) : "l"(q + (r & 1) * 4096) : "memory");
        asm volatile("{.reg .pred p; setp.eq.u32 p,%1,0xffffffff; @p trap; mov.u32 %0,%%clock;}" : "=r"(t1) : "r"(v) : "memory");
        best[r & 1] = min(best[r & 1], t1 - t0);
    }
    return best[1] < best[0];
}

struct Params {
    const uint2* m; const int* idx_in; const int* idx_out; const uint16_t* angle; const uint16_t* freq;
    const uint16_t *dist, *centers, *w_rbf, *w_sbf, *w_down, *w_up; uint2* out;
    int E, T, n1, ns, units;
    uint32_t zero; int solo;
};

__device__ __forceinline__ void red_agg(uint32_t out, uint2 v, uint32_t c2) {
    asm volatile("red.global.add.noftz.v2.bf16x2 [%0],{%1,%2};" ::"l"(g_agg + out), "r"(hmul2(v.x, c2)), "r"(hmul2(v.y, c2)) : "memory");
}
__device__ __forceinline__ void decode_entry(uint32_t e0, uint32_t e1, uint32_t& in, uint32_t& out) {
    const uint32_t bx = e1 >> 18, g = bx >= GB, rem = bx - g * GB;
    in = (g * IG + rem % IG) * SI + (e0 & 0xffff);
    out = rem / IG * SO + (e1 & 0xffff);
}
constexpr int SY_ZERO = 0, SY_END = 32, SY_EXIT = 64;
__device__ __forceinline__ void wait_zeroed(int solo) {
    if (solo) return;
    wait_flag(&g_sync[SY_ZERO], N3);
    asm volatile("fence.acquire.gpu;" ::: "memory");
}
constexpr int BAR_ATOMS = 1, BAR_STS = 2, BAR_PUB = 4, BAR_PUBFREE = 6, BAR_W = 8;
constexpr int NT_STS = (NW + 2) * 32, NT_ATOMS = (NW + 1) * 32;
__device__ __forceinline__ void mbar_arrive(uint32_t bar) {
    __syncwarp();
    if (elect_one()) asm volatile("mbarrier.arrive.shared::cta.b64 _,[%0];" ::"r"(bar) : "memory");
}
__device__ __forceinline__ void mbar_wait(uint32_t bar, uint32_t parity) {
    asm volatile("{.reg .pred p; .reg .u32 n; mov.u32 n,0;\nW: mbarrier.try_wait.parity.shared::cta.b64 p,[%0],%1; @p bra D;\n"
                 "add.u32 n,n,1; setp.lt.u32 p,n,0x4000000; @p bra W; trap;\nD:}" ::"r"(bar), "r"(parity) : "memory");
}
__device__ __forceinline__ uint32_t mad(uint32_t a, uint32_t b, uint32_t c) {
    uint32_t d; asm("mad.lo.u32 %0,%1,%2,%3;" : "=r"(d) : "r"(a), "r"(b), "r"(c)); return d;
}
template <int V> struct Mode { static constexpr int value = V; };

__device__ __forceinline__ void stage1(const Params& p, unsigned char* sm, int pid) {
    const int warp = __shfl_sync(0xffffffffu, threadIdx.x >> 5, 0), lane = threadIdx.x & 31;
    uint32_t sb = (uint32_t)__cvta_generic_to_shared(sm);
    const int ns = p.ns, nc = ns + NR + 2;
    if (ns <= 0) return;
    uint4 ra[ITERS], rb[ITERS]; uint2 rc[ITERS];
    uint32_t q = pid * (STEP / 4) + threadIdx.x;
    uint64_t pol; asm("createpolicy.fractional.L2::evict_first.b64 %0,1.0;" : "=l"(pol));
#define LOAD_IN(B, Q)                                                                                                                        \
    asm volatile("ld.global.nc.L1::no_allocate.L2::cache_hint.v4.u32 {%0,%1,%2,%3},[%4],%5;" : "=r"(ra[B].x), "=r"(ra[B].y), "=r"(ra[B].z), "=r"(ra[B].w) : "l"((const uint4*)p.idx_in + (Q)), "l"(pol)); \
    asm volatile("ld.global.nc.L1::no_allocate.L2::cache_hint.v4.u32 {%0,%1,%2,%3},[%4],%5;" : "=r"(rb[B].x), "=r"(rb[B].y), "=r"(rb[B].z), "=r"(rb[B].w) : "l"((const uint4*)p.idx_out + (Q)), "l"(pol)); \
    asm volatile("ld.global.nc.L1::no_allocate.L2::cache_hint.v2.u32 {%0,%1},[%2],%3;" : "=r"(rc[B].x), "=r"(rc[B].y) : "l"((const uint2*)p.angle + (Q)), "l"(pol));
    const uint32_t mb = sb + SM_LC;
    if (threadIdx.x < 4) asm volatile("mbarrier.init.shared::cta.b64 [%0],1;" ::"r"(mb + threadIdx.x * 8) : "memory");
    __syncthreads();
    if (warp < NW) {
        const uint32_t cb = sb + SM_CNT + (lane & p.zero), cb1 = cb + (GB - IG) * 4;
        const uint32_t xk = cb + SM_X - SM_CNT - (C / 2) * cb;
        const uint32_t ak = cb + SM_A - SM_CNT - 2 * xk;
        uint32_t cur0 = xk, nxt0 = xk + 2 * XG - C * 2, cur1 = xk, nxt1 = xk + 2 * XG - C * 2;
        uint32_t fresh = 4, n0 = 0, wpos = 0;
        uint2* const log = g_log + (pid * NW + warp) * LOGCAP;
        const uint32_t ltmask = ((1u << lane) - 1) | p.zero, cbh = cb + GB * 4;
        auto drain = [&]() {
            wait_zeroed(p.solo);
            __syncwarp();
            const float f = bf_lo(p.freq[0]);
            for (uint32_t j0 = n0 + lane; j0 < wpos + lane; j0 += 32 * 4) {
                uint2 e[4], v[4];
#pragma unroll
                for (int k = 0; k < 4; k++) e[k] = __ldcg(log + min(j0 + k * 32, wpos - 1));
                uint32_t big = 0;
#pragma unroll
                for (int k = 0; k < 4; k++) {
                    uint32_t in;
                    decode_entry(e[k].x, e[k].y - (cb << 16), in, e[k].y);
                    v[k] = __ldg(p.m + in);
                    e[k].x = __float_as_uint(rbf16(f * bf_hi(e[k].x)));
                    big = max(big, e[k].x & 0x7fffffffu);
                }
                const bool slow = __any_sync(0xffffffffu, big >= 0x42000000u);
#pragma unroll
                for (int k = 0; k < 4; k++) {
                    float c = __cosf(__uint_as_float(e[k].x));
                    if (slow) c = cos_slow(__uint_as_float(e[k].x));
                    if (j0 + k * 32 < wpos) red_agg(e[k].y, v[k], dup_bf16(c));
                }
            }
            __syncwarp();
            wpos = n0;
        };
        auto step = [&](const int s, auto mode) {
            constexpr int M = decltype(mode)::value;
            uint32_t ca[8], pa[8], aw[8], xw[8], r[8], vmask = 0xff;
#pragma unroll
            for (int h = 0; h < 2; h++) {
                if (M < 2) {
                    const uint32_t in[4] = {ra[h].x, ra[h].y, ra[h].z, ra[h].w}, out[4] = {rb[h].x, rb[h].y, rb[h].z, rb[h].w};
#pragma unroll
                    for (int k = 0; k < 4; k++) {
                        const uint32_t i = __umulhi(in[k], MI), o = __umulhi(out[k], MO);
                        aw[h * 4 + k] = __byte_perm(in[k] - i * SI, k < 2 ? rc[h].x : rc[h].y, (k & 1) ? 0x7610 : 0x5410);
                        ca[h * 4 + k] = mad(o, 64, mad(i, 4, in[k] >= IG * SI ? cb1 : cb));
                        pa[h * 4 + k] = mad(o, 64, mad(i, ASEG, ak));
                        xw[h * 4 + k] = __byte_perm(out[k] - o * SO, ca[h * 4 + k], 0x5410);
                    }
                } else {
#pragma unroll
                    for (int k = h * 4; k < h * 4 + 4; k++) {
                        const uint32_t ch = ((const uint32_t*)(sm + SM_CH))[(k * NW + warp) * NR + (s - ns)];
                        const uint2 e = __ldcg(g_log + pid * NW * LOGCAP + (ch & 0xffff) * 32 + lane);
                        const uint32_t b4 = (e.y >> 16) - cb, hi = b4 >= GB * 4, rem = b4 - (hi ? GB * 4 : 0);
                        if (lane >= (ch >> 16)) vmask ^= 1u << k;
                        aw[k] = e.x; xw[k] = e.y;
                        ca[k] = cb + (lane < (ch >> 16) ? b4 : SM_LC - SM_CNT + 128 + lane * 4);
                        pa[k] = (rem & ~63u) + ((rem & 63u) * (ASEG / 4) + (hi ? AG : 0) + ak);
                    }
                }
                if (h == 0) {
                    mbar_wait(mb + (s & 1) * 8, (s >> 1) & 1);
                }
#pragma unroll
                for (int k = h * 4; k < h * 4 + 4; k++)
                    asm volatile("atom.shared.add.u32 %0,[%1],1;" : "=r"(r[k]) : "r"(ca[k]) : "memory");
            }
            bar_arrive(BAR_ATOMS, NT_ATOMS);
            {
                mbar_wait(mb + 16 + (s & 1) * 8, (s >> 1) & 1);
            }
            uint32_t ovf = 0;
#pragma unroll
            for (int h = 0; h < 2; h++) {
#pragma unroll
                for (int k = h * 4; k < h * 4 + 4; k++) {
                    const bool lo = r[k] < C, hi = ca[k] >= cbh;
                    const uint32_t s2 = r[k] * 2 + (hi ? (lo ? cur1 : nxt1) : (lo ? cur0 : nxt0));
                    const uint32_t lim = M < 2 ? 2 * C : !((vmask >> k) & 1) ? 0 : (s == ns + NR - 1 && !hi) ? C : 2 * C;
                    asm volatile("{.reg .pred p; .reg .b16 a,b; setp.lt.u32 p,%5,%6; mov.b32 {a,b},%4; @p st.shared.u32 [%1],%2; @p st.shared.u16 [%3],a; @!p or.b32 %0,%0,%7;}"
                                 : "+r"(ovf) : "r"(pa[k] + s2 * 2), "r"(aw[k]), "r"(ca[k] * (C / 2) + s2), "r"(xw[k]), "r"(r[k]), "r"(lim), "r"(1u << k) : "memory");
                }
                if (h == 1) {
                    bar_arrive(BAR_STS + (s & 1), NT_STS);
                }
                if (M == 0) {
                    if (h == 0) q += p.n1 * (STEP / 4);
                    LOAD_IN(h, q + h * NW * 32)
                }
            }
            ovf &= vmask;
            uint32_t bal = __ballot_sync(0xffffffffu, ovf != 0);
            while (bal) {
                uint32_t e0 = aw[7], e1 = xw[7];
#pragma unroll
                for (int k = 6; k >= 0; k--)
                    if (ovf & (1u << k)) { e0 = aw[k]; e1 = xw[k]; }
                asm volatile("{.reg .pred p; setp.ne.u32 p,%3,0; @p st.global.v2.u32 [%0],{%1,%2};}" ::"l"(log + (wpos + __popc(bal & ltmask))), "r"(e0), "r"(e1), "r"(ovf) : "memory");
                wpos += __popc(bal);
                ovf &= ovf - 1;
                bal = __ballot_sync(0xffffffffu, ovf != 0);
            }
            const uint32_t nb = xk + fresh * XG - C * 2;
            if (s & 1) { cur1 = nxt1 + C * 2; nxt1 = nb - XG; } else { cur0 = nxt0 + C * 2; nxt0 = nb; }
            fresh = fresh == NP - 1 ? 0 : fresh + 1;
        };
        for (int s = 0;;) {
            LOAD_IN(0, q) LOAD_IN(1, q + NW * 32)
            for (; s < ns - 1 && wpos <= LOGCAP - 256; s++) step(s, Mode<0>());
            if (wpos <= LOGCAP - 256) break;
            drain();
        }
        step(ns - 1, Mode<1>());
        {
            uint32_t* wcnt = (uint32_t*)(sm + SM_CH + NCH * 4);
            const uint32_t nch = min((wpos + 31) / 32, (LOGCAP - 256) / 32);
            if (lane == 0) wcnt[warp] = nch;
            bar_sync(BAR_W, NW * 32);
            const uint32_t base = __reduce_add_sync(0xffffffffu, lane < warp ? wcnt[lane] : 0);
            const uint32_t mine = min(nch, NCH - min(base, NCH));
            for (uint32_t c = lane; c < mine; c += 32)
                ((uint32_t*)(sm + SM_CH))[base + c] = (warp * (LOGCAP / 32) + c) | (min(wpos - c * 32, 32u) << 16);
            n0 = min(wpos, mine * 32);
            bar_sync(BAR_W, NW * 32);
        }
        for (int s = ns; s < ns + NR; s++) {
            if (wpos > LOGCAP - 256) drain();
            step(s, Mode<2>());
        }
        for (int s = ns + NR; s < nc; s++) {
            mbar_wait(mb + (s & 1) * 8, (s >> 1) & 1);
            mbar_wait(mb + 16 + (s & 1) * 8, (s >> 1) & 1);
            bar_arrive(BAR_ATOMS, NT_ATOMS);
            bar_arrive(BAR_STS + (s & 1), NT_STS);
        }
        ;
        drain();
    } else if (warp == NW) {
        const int row = min(lane, NO - 1), swz = (row >> 1) & 3;
        mbar_arrive(mb);
        for (int s = 0; s < nc; s++) {
            uint4* cp = (uint4*)(sm + SM_CNT + (s & 1) * GB * 4) + row * 4;
            bar_sync(BAR_ATOMS, NT_ATOMS);
            uint4 c[4];
#pragma unroll
            for (int j = 0; j < 4; j++) c[j] = cp[j ^ swz];
            __syncwarp();
#pragma unroll
            for (int j = 0; j < 4; j++)
                cp[j ^ swz] = make_uint4(min(max(c[j].x, C), 2 * C) - C, min(max(c[j].y, C), 2 * C) - C,
                                         min(max(c[j].z, C), 2 * C) - C, min(max(c[j].w, C), 2 * C) - C);
            mbar_arrive(mb + ((s + 1) & 1) * 8);
            uint4 w = make_uint4(0, 0, 0, 0);
#pragma unroll
            for (int j = 0; j < 4; j++) {
                const int sh = (j ^ swz) * 8;
                w.x |= min(c[j].x, C) << sh; w.y |= min(c[j].y, C) << sh; w.z |= min(c[j].z, C) << sh; w.w |= min(c[j].w, C) << sh;
            }
            mbar_wait(mb + 16 + (s & 1) * 8, (s >> 1) & 1);
            ((uint4*)(sm + SM_CB + (s & 1) * GB))[row] = w;
            asm volatile("fence.proxy.async.shared::cta;" ::: "memory");
            bar_arrive(BAR_STS + (s & 1), NT_STS);
        }
    } else if (warp < NW + 3) {
        const int g = warp - NW - 1;
        mbar_arrive(mb + 16 + g * 8);
        const uint32_t clsf = cls_of(sm, NSL - 1, g);
        for (int s = g; s < nc; s += 2) {
            const int u = (s >> 1) * p.n1 + pid;
            const int slot = u % KA, pl = s % NP;
            const uint32_t cls = __shfl_sync(0xffffffffu, cls_of(sm, slot, g), 0);
            if (u >= KA && !p.solo) {
                wait_flag(flag_ptr(clsf, FL_S3, u - KA), NO);
                __syncwarp();
                asm volatile("fence.proxy.async.global;" ::: "memory");
            }
            bar_sync(BAR_STS + g, NT_STS);
            asm volatile("fence.proxy.async.shared::cta;" ::: "memory");
            if (elect_one()) {
                unsigned char* dst = g_ring + slot_a(slot);
#pragma unroll
                for (int j = 0; j < AG / 4096; j++)
                    asm volatile("cp.async.bulk.global.shared::cta.bulk_group [%0],[%1],4096;" ::"l"(dst + ring_off(cls, j * 4096)),
                                 "r"(sb + SM_A + pl * AG + j * 4096) : "memory");
#pragma unroll
                for (int j = 0; j * 4096 < XG; j++)
                    asm volatile("cp.async.bulk.global.shared::cta.bulk_group [%0],[%1],%2;" ::"l"(dst + ring_off(cls, AG + j * 4096)),
                                 "r"(sb + SM_X + pl * XG + j * 4096), "r"(min(4096, XG - j * 4096)) : "memory");
                asm volatile("cp.async.bulk.global.shared::cta.bulk_group [%0],[%1],%2;" ::"l"(dst + ring_off(cls, AG + XG)),
                             "r"(sb + SM_CB + g * GB), "r"(GB) : "memory");
                asm volatile("cp.async.bulk.commit_group;" ::: "memory");
                asm volatile("cp.async.bulk.wait_group 0;" ::: "memory");
            }
            __syncwarp();
            mbar_arrive(mb + 16 + g * 8);
            bar_sync(BAR_PUBFREE + g, 64);
            if (lane == 0) *(volatile uint32_t*)(sm + SM_LC + 64 + g * 4) = u;
            __syncwarp();
            bar_arrive(BAR_PUB + g, 64);
        }
    } else if (warp == NW + 3) {
        uint64_t pol2; asm("createpolicy.fractional.L2::evict_normal.b64 %0,1.0;" : "=l"(pol2));
        const uint32_t clsf = cls_of(sm, NSL - 1, 0);
        bar_arrive(BAR_PUBFREE, 64);
        bar_arrive(BAR_PUBFREE + 1, 64);
        for (int s = 0; s < nc; s++) {
            const int g = s & 1;
            bar_sync(BAR_PUB + g, 64);
            const int u = *(volatile uint32_t*)(sm + SM_LC + 64 + g * 4);
            if (s + 2 < nc) bar_arrive(BAR_PUBFREE + g, 64);
            if (elect_one()) asm volatile("st.release.gpu.global.u32 [%0],1;" ::"l"(flag_ptr(clsf ^ (g ? ~0u : 0u), FL_READY, u)) : "memory");
            __syncwarp();
            if (2 > 0 && s + 2 + 2 < ns && elect_one()) {
                const int r0 = ((s + 2 + 2) * p.n1 + pid) * STEP;
                if (7 & 1) asm volatile("cp.async.bulk.prefetch.L2.global.L2::cache_hint [%0],%1,%2;" ::"l"(p.idx_in + r0), "r"(STEP * 4), "l"(pol2) : "memory");
                if (7 & 2) asm volatile("cp.async.bulk.prefetch.L2.global.L2::cache_hint [%0],%1,%2;" ::"l"(p.idx_out + r0), "r"(STEP * 4), "l"(pol2) : "memory");
                if (7 & 4) asm volatile("cp.async.bulk.prefetch.L2.global.L2::cache_hint [%0],%1,%2;" ::"l"(p.angle + r0), "r"(STEP * 2), "l"(pol2) : "memory");
            }
            __syncwarp();
        }
    }
}

__device__ __forceinline__ void stage2(const Params& p, unsigned char* sm, int g, int ig) {
    const int warp = threadIdx.x >> 5, lane = threadIdx.x & 31;
    uint32_t sb = (uint32_t)__cvta_generic_to_shared(sm);
    const uint32_t mb = sb + SM_AUX + AUX_MISC + 16;
    if (warp == 0) {
        const int e0 = (g * IG + ig) * SI, bytes = max(0, min((int)SI, p.E - e0)) * 8;
        if (elect_one()) {
            asm volatile("mbarrier.init.shared::cta.b64 [%0],1;" ::"r"(mb) : "memory");
            asm volatile("fence.proxy.async.shared::cta;" ::: "memory");
            asm volatile("mbarrier.arrive.expect_tx.shared::cta.b64 _,[%0],%1;" ::"r"(mb), "r"(bytes) : "memory");
            for (int o = 0; o < bytes; o += 16384)
                asm volatile("cp.async.bulk.shared::cluster.global.mbarrier::complete_tx::bytes [%0],[%1],%2,[%3];" ::"r"(sb + o), "l"((const char*)(p.m + e0) + o), "r"(min(16384, bytes - o)), "r"(mb) : "memory");
        }
        __syncwarp();
    }
    uint2* tab_a = (uint2*)(sm + SM_AUX + AUX_TAB);
    uint32_t* tab_v = (uint32_t*)(tab_a + KA);
    const uint32_t a0 = ig * ASEG, a1 = (a0 + ASEG - 1) & ~4095u;
    if (threadIdx.x < KA) {
        const uint32_t cls = cls_of(sm, threadIdx.x, g);
        tab_a[threadIdx.x] = make_uint2(slot_a(threadIdx.x) + ring_off(cls, a0), slot_a(threadIdx.x) + ring_off(cls, a1) - (a1 - a0));
    } else if (threadIdx.x < KA + KV) tab_v[threadIdx.x - KA] = cls_of(sm, threadIdx.x, g);
    if (threadIdx.x < 32) ((uint32_t*)(sm + SM_AUX + AUX_PUB))[threadIdx.x] = 0;
    const uint32_t pub = sb + SM_AUX + AUX_PUB;
    __syncthreads();
    constexpr int NCW = 31, STEPS = NO / 4;
    const uint32_t clsf = cls_of(sm, NSL - 1, g);
    if (warp == NCW) { poller<NCW>(clsf, p.solo ? 0 : 1, FL_S3, KV, p.solo ? 0 : NO, p.units, pub, 0x7fffffff, [] {}); return; }
    mbar_wait(mb, 0);
    asm volatile("mov.u32 %0,%0;" : "+r"(sb));
    const uint32_t f2 = (uint32_t)p.freq[0] * 0x10001u;
    const int jsplit = a1 > a0 ? (a1 - a0) / 256 : 0;
    const uint32_t vlane = (lane >> 4) * 8192 + ((lane >> 3) & 1) * VSEG + ig * 128 + (lane & 7) * 16;
    int sa = warp, sv = warp;
    uint32_t pass = 0;
    for (int u = warp; u < p.units; u += NCW) {
        const uint32_t tag = pass;
        const uint2 ta = tab_a[sa];
        const uint32_t cq = (tab_v[sv] >> (lane >> 4)) << 12;
        const uint32_t vo = slot_v(sv) + vlane;
        const unsigned char* ap0 = g_ring + ta.x + lane * 8;
        const unsigned char* ap1 = g_ring + ta.y + lane * 8;
        sa += NCW; if (sa >= KA) sa -= KA;
        sv += NCW; if (sv >= KV) { sv -= KV; pass ^= 1; }
        wait_pub(pub + warp * 4, u);
        uint2 a[STEPS];
#pragma unroll
        for (int j = 0; j < STEPS; j++) a[j] = __ldcg((const uint2*)((j < jsplit ? ap0 : ap1) + j * 256));
        uint32_t big = 0;
#pragma unroll
        for (int j = 0; j < STEPS; j++) big |= (hmul2(__byte_perm(a[j].x, a[j].y, 0x7632), f2) & 0x7fff7fffu) + 0x3e003e00u;
        const bool slow = __any_sync(0xffffffffu, big & 0x80008000u);
#pragma unroll
        for (int j = 0; j < STEPS; j++) {
            uint2 m0, m1;
            asm volatile("ld.shared.v2.u32 {%0,%1},[%2];" : "=r"(m0.x), "=r"(m0.y) : "r"(sb + (a[j].x & 0xffff) * 8));
            asm volatile("ld.shared.v2.u32 {%0,%1},[%2];" : "=r"(m1.x), "=r"(m1.y) : "r"(sb + (a[j].y & 0xffff) * 8));
            const uint32_t x2 = hmul2(__byte_perm(a[j].x, a[j].y, 0x7632), f2);
            float c0 = __cosf(bf_lo(x2)), c1 = __cosf(bf_hi(x2));
            if (slow) { c0 = cos_slow(bf_lo(x2)); c1 = cos_slow(bf_hi(x2)); }
            const uint32_t d0 = dup_bf16(c0), d1 = dup_bf16(c1);
            st128(g_ring + (vo | ((cq >> (2 * j)) & 0x1000)) + j * 16384,
                  make_uint4((hmul2(m0.x, d0) & ~1u) | tag, hmul2(m0.y, d0), hmul2(m1.x, d1), hmul2(m1.y, d1)));
        }
        __syncwarp();
        if (u < KV) asm volatile("fence.acq_rel.gpu;" ::: "memory");
        if (lane == 0) asm volatile("red.relaxed.gpu.global.add.u32 [%0],1;" ::"l"(flag_ptr(clsf, FL_S2, u)) : "memory");
    }
    wait_zeroed(p.solo);
    const float f = bf_lo(p.freq[0]);
    for (int t0 = p.ns * p.n1 * STEP + (g * IG + ig) * NCW * 32 + threadIdx.x; t0 < p.T; t0 += 4 * N2 * NCW * 32) {
        uint32_t in[4], out[4], an[4]; uint2 v[4];
#pragma unroll
        for (int k = 0; k < 4; k++) {
            const int t = min(t0 + k * N2 * NCW * 32, p.T - 1);
            in[k] = p.idx_in[t]; out[k] = p.idx_out[t]; an[k] = p.angle[t];
        }
#pragma unroll
        for (int k = 0; k < 4; k++) v[k] = __ldg(p.m + in[k]);
#pragma unroll
        for (int k = 0; k < 4; k++)
            if (t0 + k * N2 * NCW * 32 < p.T) red_agg(out[k], v[k], dup_bf16(cos_any(rbf16(f * bf_lo(an[k])))));
    }
}

__device__ __forceinline__ uint2 lock64(uint32_t a) {
    uint2 r;
    asm volatile("{.reg .b64 y; atom.shared.exch.b64 y,[%2],0xffffffffffffffff; mov.b64 {%0,%1},y;}" : "=r"(r.x), "=r"(r.y) : "r"(a) : "memory");
    return r;
}

__device__ __forceinline__ void stage3(const Params& p, unsigned char* sm, int g, int o) {
    const int warp = threadIdx.x >> 5, lane = threadIdx.x & 31;
    uint32_t sb = (uint32_t)__cvta_generic_to_shared(sm);
    uint2* tab_a = (uint2*)(sm + SM_AUX + AUX_TAB);
    uint32_t* tab_v = (uint32_t*)(tab_a + KA);
    if (threadIdx.x < KA) {
        const uint32_t cls = cls_of(sm, threadIdx.x, g);
        tab_a[threadIdx.x] = make_uint2(slot_a(threadIdx.x) + ring_off(cls, AG + o * XSEG), slot_a(threadIdx.x) + ring_off(cls, AG + XG + o * IG));
    } else if (threadIdx.x < KA + KV) tab_v[threadIdx.x - KA] = slot_v(threadIdx.x - KA) + ring_off(cls_of(sm, threadIdx.x, g), o * VSEG);
    if (threadIdx.x < 32) ((uint32_t*)(sm + SM_AUX + AUX_PUB))[threadIdx.x] = 0;
    if (threadIdx.x < 64) ((uint32_t*)(sm + SM_AUX + AUX_DUMMY))[threadIdx.x] = ~0u;
    const uint32_t pub = sb + SM_AUX + AUX_PUB;
    for (int i = (g * NO + o) * 1024 + threadIdx.x; i < NO * (int)SO / 2; i += N3 * 1024) ((uint4*)g_agg)[i] = make_uint4(0, 0, 0, 0);
    __syncthreads();
    if (threadIdx.x == 0) asm volatile("red.release.gpu.global.add.u32 [%0],1;" ::"l"(&g_sync[SY_ZERO]) : "memory");
    constexpr int NCW = 31, STEPS = IG / 4;
    const uint32_t clsf = cls_of(sm, NSL - 1, g);
    if (warp == NCW) {
        poller<NCW>(clsf, p.solo ? 0 : 1, FL_S2, 0, p.solo ? 0 : IG, p.units, pub, p.units - 4 * p.n1, [&] {
            constexpr int H = (SO / 2 + 7) & ~7;
            const int e0 = (o * SO + g * H) & ~7, n = min(H + 8, p.E - e0) & ~7;
            if (n > 0 && elect_one()) {
                asm volatile("cp.async.bulk.prefetch.L2.global [%0],%1;" ::"l"(p.m + e0), "r"(n * 8) : "memory");
                asm volatile("cp.async.bulk.prefetch.L2.global [%0],%1;" ::"l"(g_agg + e0), "r"(n * 8) : "memory");
                asm volatile("cp.async.bulk.prefetch.L2.global [%0],%1;" ::"l"(p.dist + e0), "r"(n * 2) : "memory");
            }
            __syncwarp();
        });
        wait_zeroed(p.solo);
    }
    else {
        asm volatile("mov.u32 %0,%0;" : "+r"(sb));
        const uint32_t dummy = sb + SM_AUX + AUX_DUMMY + lane * 8, r0 = (lane & 7) * 2;
        int sa = warp, sv = warp;
        uint32_t pass = 0;
        for (int u = warp; u < p.units; u += NCW) {
            const uint32_t tag = pass;
            const uint2 ta = tab_a[sa];
            const uint4* vp = (const uint4*)(g_ring + tab_v[sv]) + lane;
            const uint32_t* xp = (const uint32_t*)(g_ring + ta.x) + lane;
            const uint32_t* cp = (const uint32_t*)(g_ring + ta.y) + (lane >> 3);
            sa += NCW; if (sa >= KA) sa -= KA;
            sv += NCW; if (sv >= KV) { sv -= KV; pass ^= 1; }
            wait_pub(pub + warp * 4, u);
            uint4 v[STEPS]; uint32_t x[STEPS];
            const uint32_t cn = __ldcg(cp);
#pragma unroll
            for (int j = 0; j < STEPS; j++) x[j] = __ldcg(xp + j * 32);
#pragma unroll
            for (int j = 0; j < STEPS; j++) v[j] = ld128(vp + j * 32);
            for (int spins = 0;; spins++) {
                uint32_t bad = 0;
#pragma unroll
                for (int j = 0; j < STEPS; j++) bad |= v[j].x ^ tag;
                if (!__any_sync(0xffffffffu, bad & 1) || p.solo) break;
                if (spins > (1 << 22)) __trap();

#pragma unroll
                for (int j = 0; j < STEPS; j++) v[j] = ld128(vp + j * 32);
            }
            uint32_t ad[2 * STEPS], dep = cn;
#pragma unroll
            for (int j = 0; j < STEPS; j++) {
                const uint32_t c = (cn >> (8 * j)) & 0xff;
                ad[2 * j] = r0 < c ? sb + (x[j] & 0xffff) * 8 : dummy;
                ad[2 * j + 1] = r0 + 1 < c ? sb + (x[j] >> 16) * 8 : dummy;
                dep ^= x[j];
            }
            if (lane == 0) asm volatile("red.relaxed.gpu.global.add.u32 [%0],%1;" ::"l"(flag_ptr(clsf, FL_S3, u)), "r"(1 + (dep & p.zero)) : "memory");
            uint32_t pend = 0;
#pragma unroll
            for (int j0 = 0; j0 < 2 * STEPS; j0 += 4) {
                uint2 t[4];
#pragma unroll
                for (int j = 0; j < 4; j++) t[j] = lock64(ad[j0 + j]);
#pragma unroll
                for (int j = 0; j < 4; j++) {
                    const int jj = j0 + j;
                    const uint32_t vx = (jj & 1) ? v[jj / 2].z : v[jj / 2].x, vy = (jj & 1) ? v[jj / 2].w : v[jj / 2].y;
                    asm volatile("{.reg .pred p,q; setp.ne.u32 p,%4,0xffffffff; @p st.shared.v2.u32 [%1],{%2,%3}; setp.ne.and.u32 q,%1,%5,!p; @q or.b32 %0,%0,%6;}"
                                 : "+r"(pend) : "r"(ad[jj]), "r"(hadd2(t[j].x, vx)), "r"(hadd2(t[j].y, vy)), "r"(t[j].x), "r"(dummy), "r"(1u << jj) : "memory");
                }
            }
            while (__any_sync(0xffffffffu, pend)) {
                uint32_t a = dummy, vx = 0, vy = 0;
#pragma unroll
                for (int jj = 2 * STEPS - 1; jj >= 0; jj--)
                    if (pend & (1u << jj)) { a = ad[jj]; vx = (jj & 1) ? v[jj / 2].z : v[jj / 2].x; vy = (jj & 1) ? v[jj / 2].w : v[jj / 2].y; }
                const uint2 t = lock64(a);
                asm volatile("{.reg .pred p; setp.ne.u32 p,%4,0xffffffff; @p st.shared.v2.u32 [%1],{%2,%3}; @p and.b32 %0,%0,%5;}"
                             : "+r"(pend) : "r"(a), "r"(hadd2(t.x, vx)), "r"(hadd2(t.y, vy)), "r"(t.x), "r"(pend - 1) : "memory");
            }
        }
    }
    asm volatile("fence.proxy.async.shared::cta;" ::: "memory");
    __syncthreads();
    constexpr int CH = 8192;
    if (lane == 0 && warp * CH < (int)SO * 8) {
        asm volatile("fence.proxy.async.global;" ::: "memory");
        const int bytes = min(CH, (int)SO * 8 - warp * CH);
        asm volatile("cp.reduce.async.bulk.global.shared::cta.bulk_group.add.noftz.bf16 [%0],[%1],%2;" ::"l"((char*)(g_agg + o * SO) + warp * CH), "r"(sb + warp * CH), "r"(bytes) : "memory");
        asm volatile("cp.async.bulk.commit_group;" ::: "memory");
    }
}

__device__ __forceinline__ void mma_edge(float (&c)[4], uint32_t p01, uint32_t q01, uint32_t p23, uint32_t q23, uint2 b) {
    asm("mma.sync.aligned.m16n8k16.row.col.f32.bf16.bf16.f32 {%0,%1,%2,%3},{%4,%5,%6,%7},{%8,%9},{%0,%1,%2,%3};"
        : "+f"(c[0]), "+f"(c[1]), "+f"(c[2]), "+f"(c[3]) : "r"(p01), "r"(q01), "r"(p23), "r"(q23), "r"(b.x), "r"(b.y));
}
__device__ __forceinline__ uint2 b_frag(const uint16_t* w, int j0) {
    const int lane = threadIdx.x & 31, j = j0 + ((lane >> 2) & 1);
    const uint2 v = make_uint2(w[j] | ((uint32_t)w[4 + j] << 16), w[8 + j] | ((uint32_t)w[12 + j] << 16));
    return (lane & 3) == (lane >> 3) ? v : make_uint2(0, 0);
}
__device__ __forceinline__ void edge_gates(const uint16_t* w, uint32_t d2, uint4& sp, uint4& gp) {
    uint32_t rb[2][4];
#pragma unroll
    for (int k = 0; k < 2; k++)
#pragma unroll
        for (int r = 0; r < 4; r++) {
            uint32_t x; asm("sub.rn.bf16x2 %0,%1,%2;" : "=r"(x) : "r"(__byte_perm(d2, 0, k ? 0x3232 : 0x1010)), "r"(((const uint32_t*)w)[48 + r]));
            const uint32_t t = hmul2(hmul2(x, x), 0xc120c120u);
            rb[k][r] = pack2(__expf(bf_lo(t)), __expf(bf_hi(t)));
        }
    uint32_t o[4][2];
#pragma unroll
    for (int n = 0; n < 4; n++) {
        float c[4] = {};
        mma_edge(c, rb[0][0], rb[1][0], rb[0][1], rb[1][1], b_frag(w + (n >> 1) * 32, (n & 1) * 2));
        mma_edge(c, rb[0][2], rb[1][2], rb[0][3], rb[1][3], b_frag(w + (n >> 1) * 32 + 16, (n & 1) * 2));
        o[n][0] = pack2(c[0], c[1]); o[n][1] = pack2(c[2], c[3]);
    }
    gp = make_uint4(o[0][0], o[1][0], o[0][1], o[1][1]);
    sp = make_uint4(o[2][0], o[3][0], o[2][1], o[3][1]);
}
__device__ __forceinline__ uint4 edge_finish(const uint16_t* w, uint4 a, uint4 sp, uint4 gp, uint4 mv) {
    float t0[4] = {}, t1[4] = {}, u0[4] = {}, u1[4] = {};
    mma_edge(t0, a.x, a.z, a.y, a.w, b_frag(w + 64, 0));
    mma_edge(t1, a.x, a.z, a.y, a.w, b_frag(w + 64, 2));
    const uint32_t p01 = pack2(t0[0] * bf_lo(sp.x), t0[1] * bf_hi(sp.x)), p23 = pack2(t1[0] * bf_lo(sp.y), t1[1] * bf_hi(sp.y));
    const uint32_t q01 = pack2(t0[2] * bf_lo(sp.z), t0[3] * bf_hi(sp.z)), q23 = pack2(t1[2] * bf_lo(sp.w), t1[3] * bf_hi(sp.w));
    mma_edge(u0, p01, q01, p23, q23, b_frag(w + 80, 0));
    mma_edge(u1, p01, q01, p23, q23, b_frag(w + 80, 2));
    return make_uint4(hadd2(mv.x, hmul2(pack2(u0[0], u0[1]), gp.x)), hadd2(mv.y, hmul2(pack2(u1[0], u1[1]), gp.y)),
                      hadd2(mv.z, hmul2(pack2(u0[2], u0[3]), gp.z)), hadd2(mv.w, hmul2(pack2(u1[2], u1[3]), gp.w)));
}

__device__ __forceinline__ void finish(const Params& p, unsigned char* sm) {
    __syncwarp();
    const int nb = gridDim.x, b = blockIdx.x, tid = threadIdx.x;
    const int role = ((const volatile uint32_t*)(sm + SM_AUX + AUX_MISC))[2];
    const uint16_t* w = (const uint16_t*)(sm + SM_AUX + AUX_W);
    if (role != 3) {
        __syncthreads();
        if (tid == 0) asm volatile("red.release.gpu.global.add.u32 [%0],1;" ::"l"(&g_sync[SY_END]) : "memory");
    }
    constexpr int EP = 3;
    uint4 sg[2 * EP];
    const int e0 = b * 1024 + tid, es = nb * 1024, np = p.E / 2;
#pragma unroll
    for (int k = 0; k < EP; k++) sg[2 * k].x = __ldg((const uint32_t*)p.dist + min(e0 + k * es, np - 1));
#pragma unroll
    for (int k = 0; k < EP; k++) edge_gates(w, sg[2 * k].x, sg[2 * k], sg[2 * k + 1]);
    uint4 mv[EP];
#pragma unroll
    for (int k = 0; k < EP; k++) mv[k] = __ldg((const uint4*)p.m + min(e0 + k * es, np - 1));
    if (role == 3) {
        asm volatile("cp.async.bulk.wait_group 0;" ::: "memory");
        __syncthreads();
        if (tid == 0) asm volatile("red.release.gpu.global.add.u32 [%0],1;" ::"l"(&g_sync[SY_END]) : "memory");
    }
    if (tid == 0) {
        wait_flag(&g_sync[SY_END], nb);
        asm volatile("fence.acquire.gpu;" ::: "memory");
    }
    __syncthreads();
    uint4 av[EP];
#pragma unroll
    for (int k = 0; k < EP; k++) av[k] = __ldcg((const uint4*)g_agg + min(e0 + k * es, np - 1));
#pragma unroll
    for (int k = 0; k < EP; k++) {
        const uint4 o = edge_finish(w, av[k], sg[2 * k], sg[2 * k + 1], mv[k]);
        if (e0 + k * es < np) ((uint4*)p.out)[e0 + k * es] = o;
    }
    for (int i = b * 1024 + tid; i < PFL * 512; i += es) ((uint4*)(g_ring + slot_v(KV)))[i] = make_uint4(0, 0, 0, 0);
    if (tid == 0) {
        g_info[b] = make_uint2(0, 0);
        if (atomicAdd(&g_sync[SY_EXIT], 1) == nb - 1) g_sync[SY_ZERO] = g_sync[SY_END] = g_sync[SY_EXIT] = 0;
    }
    for (int e = e0 + EP * es; (e & ~31) < np; e += es) {
        const int ec = min(e, np - 1);
        uint4 s0, s1;
        edge_gates(w, __ldg((const uint32_t*)p.dist + ec), s0, s1);
        const uint4 o = edge_finish(w, __ldcg((const uint4*)g_agg + ec), s0, s1, __ldg((const uint4*)p.m + ec));
        if (e < np) ((uint4*)p.out)[e] = o;
    }
    ;
}

__global__ void __launch_bounds__(1024, 1) main_kernel(const __grid_constant__ Params p) {
    extern __shared__ __align__(128) unsigned char sm[];
    const int nb = gridDim.x, b = blockIdx.x, tid = threadIdx.x, warp = tid >> 5;
    uint32_t* s_misc = (uint32_t*)(sm + SM_AUX + AUX_MISC);
    if (tid == 0) s_misc[0] = 0;
    __syncthreads();
    if ((tid & 31) == 0) {
        const int sl = b * 2 + (warp >> 4), j = warp & 15;
        if (warp == 31) s_misc[1] = upper_is_near(g_probe + (b & 127) * 32);
        else if (sl < NSL && j < (sl < KA ? PA : sl < KA + KV ? PV : PFL) &&
                 upper_is_near(g_ring + (sl < KA ? slot_a(sl) : slot_v(sl - KA)) + j * 8192))
            atomicOr(&s_misc[0], 1u << warp);
    }
    __syncwarp();
    __syncthreads();
    if (tid == 0) {
        uint32_t smid; asm("mov.u32 %0,%%smid;" : "=r"(smid));
        const u64 v = (u64)(s_misc[0] ^ (s_misc[1] ? ~0u : 0u)) | ((u64)(0x8000u | (s_misc[1] << 14) | (smid & 0x3fff)) << 32);
        asm volatile("st.release.gpu.global.u64 [%0],%1;" ::"l"(&g_info[b]), "l"(v) : "memory");
    }
    for (int i = tid; i < SM_AUX / 16; i += 1024) ((uint4*)sm)[i] = make_uint4(0, 0, 0, 0);
    uint16_t* s_info = (uint16_t*)(sm + SM_AUX + AUX_INFO);
    uint16_t* w = (uint16_t*)(sm + SM_AUX + AUX_W);
    if (tid < nb) {
        u64 v; int spins = 0;
        do {
            asm volatile("ld.acquire.gpu.global.u64 %0,[%1];" : "=l"(v) : "l"(&g_info[tid]) : "memory");
            if (++spins > (1 << 22)) __trap();
        } while (!(v >> 32));
        ((uint32_t*)(sm + SM_AUX + AUX_CLS))[tid] = (uint32_t)v;
        s_info[tid] = (uint16_t)(v >> 32);
    } else if (tid >= 256 && tid < 256 + 104) {
        const int j = tid - 256;
        w[j] = j < 32 ? p.w_rbf[j] : j < 64 ? p.w_sbf[j - 32] : j < 80 ? p.w_down[j - 64] : j < 96 ? p.w_up[j - 80] : p.centers[j - 96];
    }
    __syncthreads();
    int role = 0, rank = 0;
    {
        const int c = tid >> 2;
        const uint32_t me = s_info[min(c, nb - 1)];
        if (c < nb) {
#pragma unroll 4
            for (int j = tid & 3; j < nb; j += 4) {
                const uint32_t o = s_info[j];
                rank += ((o ^ me) & 0x4001) == 0 && (o > me || (o == me && j > c));
            }
        }
        rank += __shfl_xor_sync(0xffffffffu, rank, 1);
        rank += __shfl_xor_sync(0xffffffffu, rank, 2);
        const int c2 = (rank + 1) * IG / NO;
        if (c >= nb || (tid & 3)) role = 0;
        else if (rank >= NO) role = 1;
        else if (me & 1) role = 3;
        else if (c2 != rank * IG / NO) { role = 2; rank = c2 - 1; }
        else role = 1;
        rank |= (me >> 14 & 1) << 8;
        if (__syncthreads_count(role == 1) != p.n1 && role) {
            role = c < N2 ? 2 : c < N2 + N3 ? 3 : 1;
            const int r = role == 2 ? c : c - N2;
            rank = (r >> 1) | ((r & 1) << 8);
        }
        if (tid == b * 4) { s_misc[2] = role; s_misc[3] = rank; }
        const int pid = __syncthreads_count(role == 1 && c < b);
        role = s_misc[2]; rank = role == 1 ? pid : s_misc[3];
    }
    if (role == 1) { if (!p.solo || (p.solo & 1)) stage1(p, sm, rank); }
    else if (role == 2) { if (!p.solo || (p.solo & 2)) stage2(p, sm, rank >> 8, rank & 255); }
    else if (!p.solo || (p.solo & 4)) stage3(p, sm, rank >> 8, rank & 255);
    finish(p, sm);
}

__global__ void generic_scatter(const __grid_constant__ Params p) {
    const float f = bf_lo(p.freq[0]);
    for (int t = blockIdx.x * blockDim.x + threadIdx.x; t < p.T; t += gridDim.x * blockDim.x) {
        const uint2 v = __ldg(p.m + p.idx_in[t]);
        const uint32_t c2 = dup_bf16(cos_any(rbf16(f * bf_lo(p.angle[t]))));
        asm volatile("red.global.add.noftz.v2.bf16x2 [%0],{%1,%2};" ::"l"(p.out + p.idx_out[t]), "r"(hmul2(v.x, c2)), "r"(hmul2(v.y, c2)) : "memory");
    }
}
__global__ void __launch_bounds__(256) generic_finish(const __grid_constant__ Params p) {
    __shared__ __align__(16) uint16_t w[104];
    const int j = threadIdx.x, e = blockIdx.x * blockDim.x + j, ec = min(e, p.E - 1);
    if (j < 104) w[j] = j < 32 ? p.w_rbf[j] : j < 64 ? p.w_sbf[j - 32] : j < 80 ? p.w_down[j - 64] : j < 96 ? p.w_up[j - 80] : p.centers[j - 96];
    const uint2 a = p.out[ec], mv = p.m[ec];
    __syncthreads();
    uint4 s0, s1;
    edge_gates(w, p.dist[ec] * 0x10001u, s0, s1);
    const uint4 o = edge_finish(w, make_uint4(a.x, a.y, a.x, a.y), s0, s1, make_uint4(mv.x, mv.y, mv.x, mv.y));
    if (e < p.E) p.out[e] = make_uint2(o.x, o.y);
}

extern "C" void kernel_launch(void* const* d_in, const int* in_sizes, int n_in, void* d_out, int out_size) {
    static int nsm = 0;
    if (!nsm) {
        cudaDeviceGetAttribute(&nsm, cudaDevAttrMultiProcessorCount, 0);
        cudaFuncSetAttribute(main_kernel, cudaFuncAttributeMaxDynamicSharedMemorySize, SMEM_BYTES);
    }
    Params p;
    p.m = (const uint2*)d_in[0]; p.idx_in = (const int*)d_in[1]; p.idx_out = (const int*)d_in[2];
    p.angle = (const uint16_t*)d_in[4]; p.freq = (const uint16_t*)d_in[6];
    p.dist = (const uint16_t*)d_in[3]; p.centers = (const uint16_t*)d_in[5]; p.w_rbf = (const uint16_t*)d_in[7];
    p.w_sbf = (const uint16_t*)d_in[8]; p.w_down = (const uint16_t*)d_in[9]; p.w_up = (const uint16_t*)d_in[10];
    p.out = (uint2*)d_out;
    p.E = in_sizes[3]; p.T = in_sizes[1];
    p.solo = 0;
    p.zero = 0; p.n1 = nsm - N2 - N3;
    bool fast = 2 * nsm >= NSL && nsm <= MAX_CTA && p.n1 <= MAX_N1 && p.E <= E_CAP && p.E >= 8 && p.E % 2 == 0;
    if (fast) {
        p.ns = (p.T / (STEP * p.n1)) & ~1; p.units = p.ns ? ((p.ns + NR) / 2 + 1) * p.n1 : 0;
        fast = p.units <= MAX_UNITS;
    }
    if (!fast) {
        cudaMemsetAsync(d_out, 0, (size_t)p.E * 8);
        generic_scatter<<<nsm * 8, 256>>>(p);
        generic_finish<<<(p.E + 255) / 256, 256>>>(p);
        return;
    }
    main_kernel<<<nsm, 1024, SMEM_BYTES>>>(p);
}
```

```cpp
#include <cuda_runtime.h>
#include <cuda_bf16.h>
#include <stdint.h>

typedef unsigned long long u64;
constexpr uint32_t magic_of(uint32_t d) { return (uint32_t)(((1ull << 32) + d - 1) / d); }
constexpr uint32_t slice_of(uint32_t total, uint32_t n) {
    uint32_t d = ((total + n - 1) / n + 1) & ~1u;
    while (!((uint64_t)(n * d - 1) * magic_of(d) < ((uint64_t)n << 32))) d += 2;
    return d;
}
constexpr int E_CAP = 800000;
constexpr int NI = 32, NO = 28, NG = 2, IG = NI / NG;
constexpr uint32_t SI = slice_of(E_CAP, NI), SO = slice_of(E_CAP, NO);
constexpr uint32_t MI = magic_of(SI), MO = magic_of(SO);
constexpr int NCTA = 132, N2 = NI, N3 = NO * NG, N1 = NCTA - N2 - N3;
constexpr int C = 16, GB = NO * IG;
constexpr int NP = 5;
constexpr int NW = 28, STEP = NW * 256;
constexpr int NR = 4, LOGCAP = 8192, NCH = N1 * NW * NR * 8, KMAX = 4000;
static_assert(NR % 2 == 0 && NR >= 2 && NR <= 4 && NO % 4 == 0 && IG == 16, "shape");

constexpr int DA = 3, DS = 2, DV = 2, KA = DA * N1, KV = DV * N1, NSL = KA + KV + 1;
constexpr int ASEG = NO * C * 4, XSEG = IG * C * 2, VSEG = IG * C * 8;
constexpr int AG = IG * ASEG, XG = NO * XSEG, XO = IG / 2 * 4096, AXG = XO + XG + GB;
constexpr int PA = (AXG + 4095) / 4096, PV = NO * VSEG / 4096;
static_assert(2 * ASEG <= 4096 && AG == 2 * XG && (XO + XG) / 4096 == (AXG - 1) / 4096 && PA <= 15 && PV <= 14, "layout");
static_assert(DS >= DA - DV && DS <= DA && KA <= 256 && KV <= 128 && NSL <= 2 * NCTA && N1 <= 64, "ring");

constexpr uint32_t SB = 1024;
constexpr int SM_CNT = 0, SM_CB = NG * GB * 4, SM_LC = SM_CB + 2 * GB, SM_X = SM_LC + 256, SM_A = SM_X + NP * XG,
              SM_S1_END = SM_A + NP * AG;
constexpr int SM_AUX = SO * 8, QN = 256;
constexpr int AUX_Q = 0, AUX_PROG = QN * 8, AUX_CLS = AUX_PROG + 128, AUX_MISC = AUX_CLS + 576, AUX_DUMMY = AUX_MISC + 32,
              AUX_W = AUX_DUMMY + 256, AUX_END = AUX_W + 208;
constexpr int SMEM_BYTES = SM_AUX + AUX_END;
static_assert(SM_S1_END + 256 <= SM_AUX && SMEM_BYTES <= 232448 && SM_X % 128 == 0 && AUX_W % 16 == 0, "smem");

__device__ __align__(8192) unsigned char g_ring[(size_t)(KA * PA + KV * PV + 1) * 8192];
__device__ __align__(8192) unsigned char g_probe[8192];
__device__ uint2 g_log[N1 * NW * LOGCAP];
__device__ uint32_t g_chunks[NCH];
__device__ __align__(128) uint2 g_agg[NO * SO];
__device__ __align__(128) uint2 g_rep[NO * SO];
__device__ uint2 g_info[NCTA];
__device__ __align__(128) uint32_t g_sync[160];
constexpr int SY_ZERO = 0, SY_END = 32, SY_EXIT = 64, SY_WORK = 96, SY_LOG = 128;
constexpr int FL_GO2 = 0, FL_GO3 = 1;
constexpr uint32_t FL_DATA = 0x10000;

__device__ __forceinline__ float bf_lo(uint32_t v) { return __uint_as_float(v << 16); }
__device__ __forceinline__ float bf_hi(uint32_t v) { return __uint_as_float(v & 0xffff0000u); }
__device__ __forceinline__ float rbf16(float x) { return __bfloat162float(__float2bfloat16_rn(x)); }
__device__ __forceinline__ uint32_t hmul2(uint32_t a, uint32_t b) {
    uint32_t d; asm("mul.rn.bf16x2 %0,%1,%2;" : "=r"(d) : "r"(a), "r"(b)); return d;
}
__device__ __forceinline__ uint32_t hadd2(uint32_t a, uint32_t b) {
    uint32_t d; asm("add.rn.bf16x2 %0,%1,%2;" : "=r"(d) : "r"(a), "r"(b)); return d;
}
__device__ __forceinline__ uint32_t dup_bf16(float x) {
    uint32_t d; asm("cvt.rn.bf16x2.f32 %0,%1,%1;" : "=r"(d) : "f"(x)); return d;
}
__device__ __forceinline__ uint32_t pack2(float lo, float hi) {
    uint32_t d; asm("cvt.rn.bf16x2.f32 %0,%2,%1;" : "=r"(d) : "f"(lo), "f"(hi)); return d;
}
__device__ __noinline__ float cos_slow(float x) { return cosf(x); }
__device__ __forceinline__ float cos_any(float x) { return fabsf(x) < 32.f ? __cosf(x) : cos_slow(x); }
__device__ __forceinline__ void bar_sync(int id, int n) { asm volatile("barrier.sync.aligned %0,%1;" ::"r"(id), "r"(n) : "memory"); }
__device__ __forceinline__ void bar_arrive(int id, int n) { asm volatile("barrier.arrive.aligned %0,%1;" ::"r"(id), "r"(n) : "memory"); }
__device__ __forceinline__ uint32_t ld_relaxed(const uint32_t* p) {
    uint32_t v; asm volatile("ld.relaxed.gpu.global.u32 %0,[%1];" : "=r"(v) : "l"(p) : "memory"); return v;
}
__device__ __forceinline__ void st128(void* p, uint4 v) {
    asm volatile("{.reg .b64 a,b; .reg .b128 q; mov.b64 a,{%1,%2}; mov.b64 b,{%3,%4}; mov.b128 q,{a,b}; st.relaxed.gpu.global.b128 [%0],q;}" ::"l"(p), "r"(v.x), "r"(v.y), "r"(v.z), "r"(v.w) : "memory");
}
__device__ __forceinline__ uint4 ld128(const void* p) {
    uint4 v;
    asm volatile("{.reg .b64 a,b; .reg .b128 q; ld.relaxed.gpu.global.b128 q,[%4]; mov.b128 {a,b},q; mov.b64 {%0,%1},a; mov.b64 {%2,%3},b;}" : "=r"(v.x), "=r"(v.y), "=r"(v.z), "=r"(v.w) : "l"(p) : "memory");
    return v;
}
__device__ __forceinline__ void wait_flag(const uint32_t* p, uint32_t want) {
    int spins = 0;
    while ((ld_relaxed(p) & 0xffff) < want) {
        __nanosleep(50);
        if (++spins > (1 << 22)) __trap();
    }
}
__device__ __forceinline__ uint32_t slot_a(int s) { return s * (PA * 8192); }
__device__ __forceinline__ uint32_t slot_v(int s) { return KA * PA * 8192 + s * (PV * 8192); }
__device__ __forceinline__ uint32_t ring_off(uint32_t clsg, uint32_t off) {
    return ((off >> 12) << 13) + (((clsg >> (off >> 12)) & 1) << 12) + (off & 4095);
}
__device__ __forceinline__ uint32_t cls_of(const unsigned char* sm, int s, int g) {
    return ((const uint16_t*)(sm + SM_AUX + AUX_CLS))[s] ^ (g ? ~0u : 0u);
}
__device__ __forceinline__ uint32_t* flag_base(const unsigned char* sm, int g, int type) {
    return (uint32_t*)(g_ring + slot_v(KV) + ring_off(cls_of(sm, NSL - 1, g), type * 1024));
}
__device__ __forceinline__ uint32_t arrivals(int type, uint32_t k) {
    return type == FL_GO3 ? IG * ((k >> 2) + 1) : NO * ((k >> 2) + ((k & 3) >= DV));
}
__device__ __forceinline__ bool elect_one() {
    uint32_t r; asm volatile("{.reg .pred p; elect.sync _|p,0xffffffff; selp.u32 %0,1,0,p;}" : "=r"(r)); return r;
}
template <int NCW, int TYPE, class F>
__device__ __forceinline__ void poller(const unsigned char* sm, int g, int blk0, int blk1, int units, int hook_at, F hook) {
    const int lane = threadIdx.x & 31;
    constexpr uint32_t aux = SB + SM_AUX;
    constexpr int DR = TYPE == FL_GO2 ? DS : DA;
    const uint32_t lt = (1u << lane) - 1;
    const uint32_t* const fb = flag_base(sm, g, TYPE) + lane * 4;
    uint32_t ea[2][DR], ev[2][DV], k[2] = {0, 0}, want[2], v[2];
#pragma unroll
    for (int j = 0; j < 2; j++) {
        const int q = min(lane + j * 32, N1 - 1);
#pragma unroll
        for (int d = 0; d < DR; d++) {
            const uint32_t sa = q + d * N1, ca = cls_of(sm, sa, g);
            ea[j][d] = (((ca >> blk0) & 1) << 14) | (((ca >> blk1) & 1) << 15) | (sa << 16);
        }
#pragma unroll
        for (int d = 0; d < DV; d++) ev[j][d] = (cls_of(sm, KA + q + d * N1, g) & 0x3fff) | ((q + d * N1) << 24);
        want[j] = lane + j * 32 < N1 ? FL_DATA + arrivals(TYPE, 0) : ~0u;
        v[j] = 0;
    }
    int tail = 0, check = min(min(QN - N1, hook_at), units), spins = 0;
    while (true) {
        bool hit[2]; uint32_t bal[2];
#pragma unroll
        for (int j = 0; j < 2; j++) {
            hit[j] = v[j] >= want[j];
            bal[j] = __ballot_sync(0xffffffffu, hit[j]);
        }
        if (bal[0] | bal[1]) {
            asm volatile("fence.acquire.gpu;" ::: "memory");
            asm volatile("fence.acq_rel.cta;" ::: "memory");
            spins = 0;
        } else if (++spins > (1 << 22)) __trap();
#pragma unroll
        for (int j = 0; j < 2; j++) {
            const uint32_t pos = tail + __popc(bal[j] & lt);
            const uint32_t hi = (lane + j * 32) | ((k[j] & 0xff) << 6) | (k[j] < DV ? 0x4000 : 0) | ((pos + 1) << 16);
            asm volatile("{.reg .pred p; .reg .b64 q; setp.ne.u32 p,%3,0; mov.b64 q,{%1,%2}; @p st.relaxed.cta.shared.u64 [%0],q;}"
                         ::"r"(aux + AUX_Q + (pos % QN) * 8), "r"(ea[j][0] | ev[j][0]), "r"(hi), "r"((uint32_t)hit[j]) : "memory");
            tail += __popc(bal[j]);
            k[j] += hit[j];
        }
#pragma unroll
        for (int j = 0; j < 2; j++) v[j] = ld_relaxed(fb + (j && lane + 32 < N1 ? 128 : 0) + (k[j] & 3));
#pragma unroll
        for (int j = 0; j < 2; j++) {
            const uint32_t a0 = ea[j][0], v0 = ev[j][0] ^ 0x80000000u;
#pragma unroll
            for (int d = 0; d < DR; d++) ea[j][d] = hit[j] ? (d + 1 < DR ? ea[j][(d + 1) % DR] : a0) : ea[j][d];
#pragma unroll
            for (int d = 0; d < DV; d++) ev[j][d] = hit[j] ? (d + 1 < DV ? ev[j][(d + 1) % DV] : v0) : ev[j][d];
            want[j] = hit[j] ? ((k[j] >> 2) + 1) * FL_DATA + arrivals(TYPE, k[j]) : want[j];
        }
        if (tail >= check) {
            if (tail >= units) break;
            if (tail >= hook_at) { hook(); hook_at = 0x7fffffff; }
            int limit;
            do {
                int prog; asm volatile("ld.volatile.shared.u32 %0,[%1];" : "=r"(prog) : "r"(aux + AUX_PROG + min(lane, NCW - 1) * 4) : "memory");
                limit = __reduce_min_sync(0xffffffffu, prog) + QN - N1;
            } while (tail > limit);
            check = min(min(limit, hook_at), units);
        }
    }
}
template <bool BLOCK>
__device__ __forceinline__ bool next_unit(uint32_t aux, int t, int step, uint2& e) {
    u64 v;
    while (true) {
        asm volatile("ld.acquire.cta.shared.u64 %0,[%1];" : "=l"(v) : "r"(aux + AUX_Q + (t % QN) * 8) : "memory");
        if (__all_sync(0xffffffffu, (int)(v >> 48) == t + 1)) break;
        if (!BLOCK) return false;
        __nanosleep(40);
    }
    if ((threadIdx.x & 31) == 0) asm volatile("st.volatile.shared.u32 [%0],%1;" ::"r"(aux + AUX_PROG + (threadIdx.x >> 5) * 4), "r"(t + step) : "memory");
    e = make_uint2((uint32_t)v, (uint32_t)(v >> 32) & 0xffff);
    return true;
}
__device__ __forceinline__ int upper_is_near(unsigned char* q) {
    ((uint4*)q)[0] = ((uint4*)q)[1] = ((uint4*)(q + 4096))[0] = ((uint4*)(q + 4096))[1] = make_uint4(0, 0, 0, 0);
    uint32_t best[2] = {~0u, ~0u};
#pragma unroll
    for (int r = 0; r < 4; r++) {
        uint32_t t0, t1, v;
        asm volatile("mov.u32 %0,%%clock;" : "=r"(t0)::"memory");
        asm volatile("atom.global.exch.b32 %0,[%1],0;" : "=r"(v) : "l"(q + (r & 1) * 4096) : "memory");
        asm volatile("{.reg .pred p; setp.eq.u32 p,%1,0xffffffff; @p trap; mov.u32 %0,%%clock;}" : "=r"(t1) : "r"(v) : "memory");
        best[r & 1] = min(best[r & 1], t1 - t0);
    }
    return best[1] < best[0];
}

struct Params {
    const uint2* m; const int* idx_in; const int* idx_out; const uint16_t* angle; const uint16_t* freq;
    const uint16_t *dist, *centers, *w_rbf, *w_sbf, *w_down, *w_up; uint2* out;
    int E, T, pairs, units;
    uint32_t zero;
    cudaTextureObject_t tin, tout, tang;
};

__device__ __forceinline__ void red_agg(uint32_t out, uint2 v, uint32_t c2) {
    asm volatile("red.global.add.noftz.v2.bf16x2 [%0],{%1,%2};" ::"l"(g_agg + out), "r"(hmul2(v.x, c2)), "r"(hmul2(v.y, c2)) : "memory");
}
__device__ __forceinline__ void decode_entry(uint32_t e0, uint32_t e1, uint32_t& in, uint32_t& out) {
    const uint32_t bx = e1 >> 18, g = bx >= GB, rem = bx - g * GB;
    in = (g * IG + rem % IG) * SI + (e0 & 0xffff);
    out = rem / IG * SO + (e1 & 0xffff);
}
__device__ __forceinline__ void wait_zeroed() {
    wait_flag(&g_sync[SY_ZERO], N3);
    asm volatile("fence.acquire.gpu;" ::: "memory");
}
constexpr int BAR_ATOMS = 1, BAR_STS = 2, BAR_PUB = 4, BAR_PUBFREE = 6, BAR_W = 8;
constexpr int NT_STS = (NW + 2) * 32, NT_ATOMS = (NW + 1) * 32;
__device__ __forceinline__ void mbar_arrive(uint32_t bar) {
    __syncwarp();
    if (elect_one()) asm volatile("mbarrier.arrive.shared::cta.b64 _,[%0];" ::"r"(bar) : "memory");
}
__device__ __forceinline__ void mbar_wait(uint32_t bar, uint32_t parity) {
    asm volatile("{.reg .pred p; .reg .u32 n; mov.u32 n,0;\nW: mbarrier.try_wait.parity.shared::cta.b64 p,[%0],%1,2000; @p bra D;\n"
                 "add.u32 n,n,1; setp.lt.u32 p,n,0x4000000; @p bra W; trap;\nD:}" ::"r"(bar), "r"(parity) : "memory");
}
__device__ __forceinline__ uint32_t mad(uint32_t a, uint32_t b, uint32_t c) {
    uint32_t d; asm("mad.lo.u32 %0,%1,%2,%3;" : "=r"(d) : "r"(a), "r"(b), "r"(c)); return d;
}
template <bool V> struct Replay { static constexpr bool value = V; };

__device__ __forceinline__ void stage1(const Params& p, unsigned char* sm, int pid) {
    const int warp = __shfl_sync(0xffffffffu, threadIdx.x >> 5, 0), lane = threadIdx.x & 31;
    constexpr uint32_t sb = SB;
    uint4 ra[2], rb[2]; uint2 rc[2];
    volatile int* const s_next = (volatile int*)(sm + SM_LC + 64);
    const int total = p.pairs * 2;
    const uint32_t mb = sb + SM_LC;
    if (threadIdx.x < 4) asm volatile("mbarrier.init.shared::cta.b64 [%0],1;" ::"r"(mb + threadIdx.x * 8) : "memory");
    if (threadIdx.x == 0) { s_next[0] = pid * 2 + 1; s_next[2] = 0x7ffffff0; }
    if (threadIdx.x < 32) s_next[16 + threadIdx.x] = 2 * C;
    __syncthreads();
    if (warp < NW) {
        constexpr uint32_t cb = sb + SM_CNT, cb1 = cb + (GB - IG) * 4, cbh = cb + GB * 4, cdum = sb + SM_LC + 128;
        static_assert(cb % 64 == 0, "counter base");
        constexpr uint32_t xk = sb + SM_X - (C / 2) * cb, ak = sb + SM_A - 2 * xk;
        uint32_t cur0 = xk + (lane & p.zero), nxt0 = cur0 + 2 * XG - C * 2, cur1 = cur0, nxt1 = nxt0;
        uint32_t fresh = 4 + (lane & p.zero), n0 = 0, wpos = 0, chunk = 0;
        int h_in = pid * 2, ns = 0;
        uint2* const log = g_log + (pid * NW + warp) * LOGCAP;
        const uint32_t ltmask = ((1u << lane) - 1) | p.zero;
        auto load_in = [&](int h) {
            const int q = h_in * (STEP / 4) + threadIdx.x + h * NW * 32;
            asm volatile("tex.1d.v4.u32.s32 {%0,%1,%2,%3},[%4,{%5}];" : "=r"(ra[h].x), "=r"(ra[h].y), "=r"(ra[h].z), "=r"(ra[h].w) : "l"(p.tin), "r"(q));
            asm volatile("tex.1d.v4.u32.s32 {%0,%1,%2,%3},[%4,{%5}];" : "=r"(rb[h].x), "=r"(rb[h].y), "=r"(rb[h].z), "=r"(rb[h].w) : "l"(p.tout), "r"(q));
            asm volatile("{.reg .b32 z,w; tex.1d.v4.u32.s32 {%0,%1,z,w},[%2,{%3}];}" : "=r"(rc[h].x), "=r"(rc[h].y) : "l"(p.tang), "r"(q));
        };
        auto direct = [&](uint32_t first, uint32_t stride, uint32_t count, auto range) {
            wait_zeroed();
            __syncwarp();
            const float f = bf_lo(p.freq[0]);
            for (uint32_t c0 = first; c0 < count; c0 += stride * 4) {
                uint2 e[4], v[4]; uint32_t ok = 0, big = 0;
#pragma unroll
                for (int k = 0; k < 4; k++) {
                    uint32_t lo, hi;
                    range(min(c0 + k * stride, count - 1), lo, hi);
                    e[k] = __ldcg(g_log + min(lo + lane, hi - 1));
                    if (lo + lane < hi && c0 + k * stride < count) ok |= 1u << k;
                }
#pragma unroll
                for (int k = 0; k < 4; k++) {
                    uint32_t in;
                    decode_entry(e[k].x, e[k].y - (cb << 16), in, e[k].y);
                    v[k] = __ldg(p.m + in);
                    e[k].x = __float_as_uint(rbf16(f * bf_hi(e[k].x)));
                    big = max(big, e[k].x & 0x7fffffffu);
                }
                const bool slow = __any_sync(0xffffffffu, big >= 0x42000000u);
#pragma unroll
                for (int k = 0; k < 4; k++) {
                    float c = __cosf(__uint_as_float(e[k].x));
                    if (slow) c = cos_slow(__uint_as_float(e[k].x));
                    if ((ok >> k) & 1) red_agg(e[k].y, v[k], dup_bf16(c));
                }
                __syncwarp();
            }
        };
        auto drain = [&]() {
            const uint32_t lb = (pid * NW + warp) * LOGCAP;
            direct(0, 1, (wpos - n0 + 31) / 32, [&](uint32_t c, uint32_t& lo, uint32_t& hi) { lo = lb + n0 + c * 32; hi = lb + wpos; });
            wpos = n0;
        };
        auto load_log = [&](int j) {
            uint2 e[8];
#pragma unroll
            for (int k = 0; k < 8; k++) {
                const uint32_t ch = __shfl_sync(0xffffffffu, chunk, k * NR + j);
                e[k] = make_uint2(0, (cdum + lane * 4) << 16);
                if (j < NR && lane < (ch >> 24)) e[k] = __ldcg(g_log + (ch & 0xffffff) * 32 + lane);
            }
#pragma unroll
            for (int h = 0; h < 2; h++) {
                ra[h] = make_uint4(e[h * 4].x, e[h * 4].y, e[h * 4 + 1].x, e[h * 4 + 1].y);
                rb[h] = make_uint4(e[h * 4 + 2].x, e[h * 4 + 2].y, e[h * 4 + 3].x, e[h * 4 + 3].y);
            }
        };
        auto step = [&](const int s, auto replay) {
            constexpr bool R = decltype(replay)::value;
            uint32_t ca[8], pa[8], aw[8], xw[8], r[8];
#pragma unroll
            for (int h = 0; h < 2; h++) {
                if (!R) {
                    const uint32_t in[4] = {ra[h].x, ra[h].y, ra[h].z, ra[h].w}, out[4] = {rb[h].x, rb[h].y, rb[h].z, rb[h].w};
#pragma unroll
                    for (int k = 0; k < 4; k++) {
                        const uint32_t i = __umulhi(in[k], MI), o = __umulhi(out[k], MO);
                        aw[h * 4 + k] = __byte_perm(in[k] - i * SI, k < 2 ? rc[h].x : rc[h].y, (k & 1) ? 0x7610 : 0x5410);
                        ca[h * 4 + k] = mad(o, 64, mad(i, 4, in[k] >= IG * SI ? cb1 : cb));
                        pa[h * 4 + k] = mad(o, 64, i * ASEG);
                        xw[h * 4 + k] = __byte_perm(out[k] - o * SO, ca[h * 4 + k], 0x5410);
                    }
                } else {
#pragma unroll
                    for (int k = h * 4; k < h * 4 + 4; k++) {
                        const uint4 q4 = (k & 2) ? rb[h] : ra[h];
                        const uint2 e = (k & 1) ? make_uint2(q4.z, q4.w) : make_uint2(q4.x, q4.y);
                        aw[k] = e.x; xw[k] = e.y; ca[k] = e.y >> 16;
                        pa[k] = mad(ca[k] & 63u, ASEG / 4 - 1, ca[k] + (ca[k] >= cbh ? AG - cbh : 0 - cb));
                    }
                }
                if (h == 0) {
                    mbar_wait(mb + (s & 1) * 8, (s >> 1) & 1);
                    if (!R) h_in = s_next[s & 1];
                }
#pragma unroll
                for (int k = h * 4; k < h * 4 + 4; k++)
                    asm volatile("atom.shared.add.u32 %0,[%1],1;" : "=r"(r[k]) : "r"(ca[k]) : "memory");
            }
            bar_arrive(BAR_ATOMS, NT_ATOMS);
            mbar_wait(mb + 16 + (s & 1) * 8, (s >> 1) & 1);
            if (!R) {
                load_in(0);
                if (p.zero) __nanosleep(0);
            }
            uint32_t ovf = 0;
#pragma unroll
            for (int k = 0; k < 8; k++) {
                const bool lo = r[k] < C, hi = xw[k] >= cbh << 16;
                const uint32_t s2 = r[k] * 2 + (hi ? (lo ? cur1 : nxt1) : (lo ? cur0 : nxt0));
                asm volatile("{.reg .pred p; .reg .b16 a,b; setp.lt.u32 p,%5,%6; mov.b32 {a,b},%4;"
                             " @p st.shared.u32 [%1+%8],%2; @p st.shared.u16 [%3],a; @!p or.b32 %0,%0,%7;}"
                             : "+r"(ovf) : "r"(pa[k] + s2 * 2), "r"(aw[k]), "r"(mad(xw[k] >> 16, C / 2, s2)), "r"(xw[k]), "r"(r[k]),
                               "n"(2 * C), "r"(R && xw[k] >= cdum << 16 ? 0u : 1u << k), "n"(ak) : "memory");
            }
            bar_arrive(BAR_STS + (s & 1), NT_STS);
            if (!R) {
                if (p.zero) __nanosleep(0);
                load_in(1);
            } else load_log(s + 1 - ns);
            uint32_t bal = __ballot_sync(0xffffffffu, ovf != 0);
            while (bal) {
                uint32_t e0 = aw[7], e1 = xw[7];
#pragma unroll
                for (int k = 6; k >= 0; k--)
                    if (ovf & (1u << k)) { e0 = aw[k]; e1 = xw[k]; }
                asm volatile("{.reg .pred p; setp.ne.u32 p,%3,0; @p st.global.v2.u32 [%0],{%1,%2};}" ::"l"(log + (wpos + __popc(bal & ltmask))), "r"(e0), "r"(e1), "r"(ovf) : "memory");
                wpos += __popc(bal);
                ovf &= ovf - 1;
                bal = __ballot_sync(0xffffffffu, ovf != 0);
            }
            const uint32_t nb = xk + fresh * XG - C * 2;
            if (s & 1) { cur1 = nxt1 + C * 2; nxt1 = nb - XG; }
            else if (!R || s != ns + NR - 2) { cur0 = nxt0 + C * 2; nxt0 = nb; }
            fresh = fresh == NP - 1 ? 0 : fresh + 1;
        };
        u64* const logsync = (u64*)&g_sync[SY_LOG];
        for (int stop = total - 2 * 2 * N1; h_in < total;) {
            load_in(0); load_in(1);
            do { step(ns, Replay<false>()); ns++; } while (h_in < stop && wpos <= LOGCAP - 256);
            if (wpos > LOGCAP - 256) drain();
            if (h_in >= stop && stop < total) {
                const uint32_t nch = min((wpos + 31) / 32, (LOGCAP - 256 * NR) / 32);
                uint32_t base = 0;
                if (lane == 0) base = (uint32_t)atomicAdd(logsync, (u64)nch);
                base = __shfl_sync(0xffffffffu, base, 0);
                const uint32_t mine = min(nch, NCH - min(base, NCH));
                for (uint32_t c = lane; c < mine; c += 32)
                    g_chunks[base + c] = ((pid * NW + warp) * (LOGCAP / 32) + c) | (min(wpos - c * 32, 32u) << 24);
                n0 = min(wpos, mine * 32);
                __syncwarp();
                if (elect_one()) {
                    asm volatile("red.release.gpu.global.add.u64 [%0],%1;" ::"l"(logsync), "l"(1ull << 32) : "memory");
                    if (n0 >= 2) asm volatile("cp.async.bulk.prefetch.L2.global [%0],%1;" ::"l"(log), "r"(n0 / 2 * 16) : "memory");
                }
                __syncwarp();
                stop = total;
            }
        }
        {
            u64 v; int spins = 0;
            do {
                asm volatile("ld.acquire.gpu.global.u64 %0,[%1];" : "=l"(v) : "l"(logsync) : "memory");
                if (++spins > (1 << 22)) __trap();
            } while ((v >> 32) < N1 * NW);
            const uint32_t idx = (((lane / NR) * NW + warp) * NR + lane % NR) * N1 + pid;
            if (lane < 8 * NR && idx < (uint32_t)v) chunk = __ldcg(g_chunks + idx);
            __syncwarp();
        }
        if (wpos > LOGCAP - 256 * NR) drain();
        load_log(0);
        for (int s = ns; s < ns + NR; s++) step(s, Replay<true>());
        for (int s = ns + NR; s < ns + NR + 2; s++) {
            mbar_wait(mb + (s & 1) * 8, (s >> 1) & 1);
            mbar_wait(mb + 16 + (s & 1) * 8, (s >> 1) & 1);
            bar_arrive(BAR_ATOMS, NT_ATOMS);
            bar_arrive(BAR_STS + (s & 1), NT_STS);
        }
        uint2* const rng = (uint2*)(sm + SM_S1_END);
        if (lane == 0) rng[warp] = make_uint2(n0, wpos);
        bar_sync(BAR_W, (NW + 1) * 32);
        const uint2 mine = lane < NW ? rng[lane] : make_uint2(0, 0);
        const uint32_t nch = (mine.y - mine.x + 31) / 32;
        uint32_t end = nch;
#pragma unroll
        for (int d = 1; d < 32; d *= 2) {
            const uint32_t t = __shfl_up_sync(0xffffffffu, end, d);
            if (lane >= d) end += t;
        }
        direct(warp, NW, __shfl_sync(0xffffffffu, end, 31), [&](uint32_t c, uint32_t& lo, uint32_t& hi) {
            const int w = __popc(__ballot_sync(0xffffffffu, end <= c));
            const uint32_t lb = (pid * NW + w) * LOGCAP;
            lo = lb + __shfl_sync(0xffffffffu, mine.x + (c - (end - nch)) * 32, w);
            hi = lb + __shfl_sync(0xffffffffu, mine.y, w);
        });
    } else if (warp == NW) {
        const int row = min(lane, NO - 1), swz = (row >> 1) & 3;
        mbar_arrive(mb);
        int pn = N1 + pid, pnn = 0, nc = 0x7ffffff0;
        for (int s = 0; s < nc; s++) {
            const int hn = min(pn * 2 + (s & 1), total);
            if (hn == total) nc = min(nc, s + 2 + NR + 2);
            const uint32_t sub = s == nc - 4 ? 0 : C, bias = s == nc - 2 ? C : 0;
            uint4* cp = (uint4*)(sm + SM_CNT + (s & 1) * GB * 4) + row * 4;
            bar_sync(BAR_ATOMS, NT_ATOMS);
            uint4 c[4];
#pragma unroll
            for (int j = 0; j < 4; j++) c[j] = cp[j ^ swz];
            __syncwarp();
#pragma unroll
            for (int j = 0; j < 4; j++)
                cp[j ^ swz] = make_uint4(min(max(c[j].x, C), 2 * C) - sub, min(max(c[j].y, C), 2 * C) - sub,
                                         min(max(c[j].z, C), 2 * C) - sub, min(max(c[j].w, C), 2 * C) - sub);
            if (lane == 0) { s_next[(s + 1) & 1] = hn; s_next[2] = nc; }
            mbar_arrive(mb + ((s + 1) & 1) * 8);
            uint4 w = make_uint4(0, 0, 0, 0);
#pragma unroll
            for (int j = 0; j < 4; j++) {
                const int sh = (j ^ swz) * 8;
                w.x |= min(c[j].x - bias, C) << sh; w.y |= min(c[j].y - bias, C) << sh;
                w.z |= min(c[j].z - bias, C) << sh; w.w |= min(c[j].w - bias, C) << sh;
            }
            mbar_wait(mb + 16 + (s & 1) * 8, (s >> 1) & 1);
            ((uint4*)(sm + SM_CB + (s & 1) * GB))[row] = w;
            asm volatile("fence.proxy.async.shared::cta;" ::: "memory");
            bar_arrive(BAR_STS + (s & 1), NT_STS);
            if (s & 1) pn = min(2 * N1 + __shfl_sync(0xffffffffu, pnn, 0), p.pairs);
            else if (hn < total && s / 2 + 2 < KMAX) {
                if (lane == 0) asm volatile("atom.relaxed.gpu.global.add.u32 %0,[%1],1;" : "=r"(pnn) : "l"(&g_sync[SY_WORK]) : "memory");
            } else pnn = p.pairs;
            const int hp = pn * 2 + ((s & 1) ^ 1);
            if (hp < total && elect_one())
                asm volatile("cp.async.bulk.prefetch.L2.global [%0],%1;" ::"l"(p.angle + hp * STEP), "r"(STEP * 2) : "memory");
            __syncwarp();
        }
    } else if (warp < NW + 3) {
        const int g = warp - NW - 1;
        mbar_arrive(mb + 16 + g * 8);
        const uint32_t* const fb = flag_base(sm, g, lane & 1) + pid * 4;
        for (int s = g; s < s_next[2]; s += 2) {
            const int k = s >> 1, slot = k % DA * N1 + pid, slots = k % DS * N1 + pid, pl = s % NP;
            const uint32_t cls = __shfl_sync(0xffffffffu, cls_of(sm, slot, g), 0), clss = __shfl_sync(0xffffffffu, cls_of(sm, slots, g), 0);
            if (k >= DS) {
                const uint32_t kw = k - ((lane & 1) ? DS : DA - DV);
                wait_flag(fb + (kw & 3), arrivals(lane & 1, kw));
                __syncwarp();
                asm volatile("fence.proxy.async.global;" ::: "memory");
            }
            bar_sync(BAR_STS + g, NT_STS);
            asm volatile("fence.proxy.async.shared::cta;" ::: "memory");
            if (elect_one()) {
                unsigned char* dst = g_ring + slot_a(slot);
#pragma unroll
                for (int j = 0; j < IG / 2; j++)
                    asm volatile("cp.async.bulk.global.shared::cta.bulk_group [%0],[%1],%2;" ::"l"(g_ring + slot_a(slots) + ring_off(clss, j * 4096)),
                                 "r"(sb + SM_A + pl * AG + j * 2 * ASEG), "n"(2 * ASEG) : "memory");
#pragma unroll
                for (int j = 0; j * 4096 < XG; j++)
                    asm volatile("cp.async.bulk.global.shared::cta.bulk_group [%0],[%1],%2;" ::"l"(dst + ring_off(cls, XO + j * 4096)),
                                 "r"(sb + SM_X + pl * XG + j * 4096), "r"(min(4096, XG - j * 4096)) : "memory");
                asm volatile("cp.async.bulk.global.shared::cta.bulk_group [%0],[%1],%2;" ::"l"(dst + ring_off(cls, XO + XG)),
                             "r"(sb + SM_CB + g * GB), "r"(GB) : "memory");
                asm volatile("cp.async.bulk.commit_group;" ::: "memory");
                asm volatile("cp.async.bulk.wait_group 0;" ::: "memory");
            }
            __syncwarp();
            mbar_arrive(mb + 16 + g * 8);
            bar_sync(BAR_PUBFREE + g, 64);
            bar_arrive(BAR_PUB + g, 64);
        }
    } else if (warp == NW + 3) {
        uint32_t* const fb = flag_base(sm, (lane >> 1) & 1, lane & 1) + pid * 4;
        bar_arrive(BAR_PUBFREE, 64);
        bar_arrive(BAR_PUBFREE + 1, 64);
        for (int s = 0; s < s_next[2]; s++) {
            const int g = s & 1;
            bar_sync(BAR_PUB + g, 64);
            if (s + 2 < s_next[2]) bar_arrive(BAR_PUBFREE + g, 64);
            asm volatile("fence.acq_rel.gpu;" ::: "memory");
            if ((lane >> 1) == g) asm volatile("red.relaxed.gpu.global.add.u32 [%0],%1;" ::"l"(fb + ((s >> 1) & 3)), "r"(FL_DATA) : "memory");
            __syncwarp();
        }
        bar_arrive(BAR_W, (NW + 1) * 32);
    }
}

__device__ __forceinline__ void stage2(const Params& p, unsigned char* sm, int g, int ig) {
    const int warp = threadIdx.x >> 5, lane = threadIdx.x & 31;
    constexpr uint32_t sb = SB;
    constexpr int NCW = 15, STEPS = NO / 4, TAB = NCW * ASEG, MB = TAB + SI * 8;
    static_assert(MB + 8 * NCW + 8 <= SM_AUX && MB % 8 == 0, "stage2 smem");
    if (threadIdx.x <= NCW) asm volatile("mbarrier.init.shared::cta.b64 [%0],1;" ::"r"(sb + MB + threadIdx.x * 8) : "memory");
    asm volatile("fence.proxy.async.shared::cta;" ::: "memory");
    __syncthreads();
    if (warp == 30) {
        const int e0 = (g * IG + ig) * SI, bytes = max(0, min((int)SI, p.E - e0)) * 8;
        if (elect_one()) {
            asm volatile("mbarrier.arrive.expect_tx.shared::cta.b64 _,[%0],%1;" ::"r"(sb + MB + NCW * 8), "r"(bytes) : "memory");
            for (int o = 0; o < bytes; o += 16384)
                asm volatile("cp.async.bulk.shared::cluster.global.mbarrier::complete_tx::bytes [%0],[%1],%2,[%3];" ::"r"(sb + TAB + o), "l"((const char*)(p.m + e0) + o), "r"(min(16384, bytes - o)), "r"(sb + MB + NCW * 8) : "memory");
        }
        __syncwarp();
    }
    if (warp == 31) poller<NCW, FL_GO2>(sm, g, ig >> 1, 0, p.units, 0x7fffffff, [] {});
    if (warp >= NCW) return;
    uint32_t* const fb = flag_base(sm, g, FL_GO3);
    const uint32_t f2 = (uint32_t)p.freq[0] * 0x10001u;
    const uint32_t vlane = slot_v(0) + (lane >> 4) * 8192 + ((lane >> 3) & 1) * VSEG + ig * 128 + (lane & 7) * 16;
    const uint32_t aoff = (ig >> 1) * 8192 + (ig & 1) * ASEG, buf = sb + warp * ASEG, mb = sb + MB + warp * 8;
    auto fetch = [&](uint32_t e) {
        if (elect_one()) {
            asm volatile("fence.proxy.async.global;" ::: "memory");
            asm volatile("mbarrier.arrive.expect_tx.shared::cta.b64 _,[%0],%1;" ::"r"(mb), "n"(ASEG) : "memory");
            asm volatile("cp.async.bulk.shared::cluster.global.mbarrier::complete_tx::bytes [%0],[%1],%2,[%3];" ::"r"(buf),
                         "l"(g_ring + (slot_a((e >> 16) & 0xff) + aoff + ((e >> 2) & 0x1000))), "n"(ASEG), "r"(mb) : "memory");
        }
        __syncwarp();
    };
    mbar_wait(sb + MB + NCW * 8, 0);
    uint2 qn = make_uint2(0, 0);
    bool have = false;
    uint32_t ph = 0;
    for (int t = warp; t < p.units; t += NCW) {
        if (!have) { next_unit<true>(sb + SM_AUX, t, NCW, qn); fetch(qn.x); }
        const uint2 qe = qn;
        mbar_wait(mb, ph); ph ^= 1;
        uint2 a[STEPS];
#pragma unroll
        for (int j = 0; j < STEPS; j++) asm volatile("ld.shared.v2.u32 {%0,%1},[%2];" : "=r"(a[j].x), "=r"(a[j].y) : "r"(buf + j * 256 + lane * 8) : "memory");
        have = next_unit<false>(sb + SM_AUX, t + NCW, NCW, qn);
        uint32_t big = 0, x2[STEPS];
#pragma unroll
        for (int j = 0; j < STEPS; j++) {
            x2[j] = hmul2(__byte_perm(a[j].x, a[j].y, 0x7632), f2);
            a[j].x = __byte_perm(a[j].x, a[j].y, 0x5410);
            big |= (x2[j] & 0x7fff7fffu) + 0x3e003e00u;
        }
        const bool slow = __any_sync(0xffffffffu, big & 0x80008000u);
        if (have) fetch(qn.x + ((uint32_t)slow & p.zero));
        if (slow) {
#pragma unroll
            for (int j = 0; j < STEPS; j++) x2[j] = pack2(cos_slow(bf_lo(x2[j])), cos_slow(bf_hi(x2[j])));
        }
        const uint32_t tag = qe.x >> 31, cq = (qe.x >> (lane >> 4)) << 12;
        const uint32_t vo = ((qe.x >> 24) & 0x7f) * (PV * 8192) + vlane;
        uint2 m0[STEPS], m1[STEPS];
#pragma unroll
        for (int jj = 0; jj < STEPS + 1; jj++) {
            if (jj < STEPS) {
                asm volatile("ld.shared.v2.u32 {%0,%1},[%2];" : "=r"(m0[jj].x), "=r"(m0[jj].y) : "r"(sb + TAB + (a[jj].x & 0xffff) * 8) : "memory");
                asm volatile("ld.shared.v2.u32 {%0,%1},[%2];" : "=r"(m1[jj].x), "=r"(m1[jj].y) : "r"(sb + TAB + (a[jj].x >> 16) * 8) : "memory");
            }
            if (jj >= 1) {
                const int j = jj - 1;
                const uint32_t cf = pack2(__cosf(bf_lo(x2[j])), __cosf(bf_hi(x2[j]))), c2 = slow ? x2[j] : cf;
                const uint32_t d0 = __byte_perm(c2, 0, 0x1010), d1 = __byte_perm(c2, 0, 0x3232);
                st128(g_ring + (vo | ((cq >> (2 * j)) & 0x1000)) + j * 16384,
                      make_uint4((hmul2(m0[j].x, d0) & ~1u) | tag, hmul2(m0[j].y, d0), hmul2(m1[j].x, d1), hmul2(m1[j].y, d1)));
                if (p.zero) __nanosleep(0);
            }
        }
        __syncwarp();
        if (qe.y & 0x4000) asm volatile("fence.acq_rel.gpu;" ::: "memory");
        if (lane == 0) asm volatile("red.relaxed.gpu.global.add.u32 [%0],1;" ::"l"(fb + (qe.y & 63) * 4 + ((qe.y >> 6) & 3)) : "memory");
    }
}

__device__ __forceinline__ uint2 lock64(uint32_t a) {
    uint2 r;
    asm volatile("{.reg .b64 y; atom.shared.exch.b64 y,[%2],0xffffffffffffffff; mov.b64 {%0,%1},y;}" : "=r"(r.x), "=r"(r.y) : "r"(a) : "memory");
    return r;
}

__device__ __forceinline__ void stage3(const Params& p, unsigned char* sm, int g, int o) {
    const int warp = threadIdx.x >> 5, lane = threadIdx.x & 31;
    constexpr uint32_t sb = SB;
    if (threadIdx.x < 64) ((uint32_t*)(sm + SM_AUX + AUX_DUMMY))[threadIdx.x] = ~0u;
    for (int i = (g * NO + o) * 1024 + threadIdx.x; i < NO * (int)SO / 2; i += N3 * 1024) ((uint4*)g_agg)[i] = make_uint4(0, 0, 0, 0);
    __syncthreads();
    if (threadIdx.x == 0) asm volatile("red.release.gpu.global.add.u32 [%0],1;" ::"l"(&g_sync[SY_ZERO]) : "memory");
    const int t0 = p.pairs * 2 * STEP + (g * NO + o) * 1024 + threadIdx.x;
    static_assert(2 * STEP <= N3 * 1024, "remainder");
    if (t0 - lane < p.T) {
        const int t = min(t0, p.T - 1);
        const uint2 v = __ldg(p.m + p.idx_in[t]);
        wait_zeroed();
        if (t0 < p.T) red_agg(p.idx_out[t], v, dup_bf16(cos_any(rbf16(bf_lo(p.freq[0]) * bf_lo(p.angle[t])))));
        __syncwarp();
    }
    constexpr int NCW = 22, STEPS = IG / 4;
    uint32_t* const fb = flag_base(sm, g, FL_GO2);
    if (warp == 31) {
        poller<NCW, FL_GO3>(sm, g, (XO + o * XSEG) >> 12, (XO + XG) >> 12, p.units, p.units - 1 * N1, [&] {
            constexpr int H = (SO / 2 + 7) & ~7;
            const int e0 = (o * SO + g * H) & ~7, n = min(H + 8, p.E - e0) & ~7;
            if (n > 0 && elect_one()) {
                asm volatile("cp.async.bulk.prefetch.L2.global [%0],%1;" ::"l"(p.m + e0), "r"(n * 8) : "memory");
                asm volatile("cp.async.bulk.prefetch.L2.global [%0],%1;" ::"l"(g_agg + e0), "r"(n * 8) : "memory");
                asm volatile("cp.async.bulk.prefetch.L2.global [%0],%1;" ::"l"(p.dist + e0), "r"(n * 2) : "memory");
            }
            __syncwarp();
        });
        wait_zeroed();
    } else if (warp < NCW) {
        const uint32_t dummy = sb + SM_AUX + AUX_DUMMY + lane * 8, r0 = (lane & 7) * 2;
        const uint32_t vlane = slot_v(0) + ring_off(0, o * VSEG) + lane * 16, xlane = ring_off(0, XO + o * XSEG) + lane * 4;
        const uint32_t clane = ring_off(0, XO + XG + o * IG) + (lane >> 3) * 4;
        for (int t = warp; t < p.units; t += NCW) {
            uint2 qe;
            next_unit<true>(sb + SM_AUX, t, NCW, qe);
            const uint32_t tag = qe.x >> 31, ab = slot_a((qe.x >> 16) & 0xff);
            const uint4* vp = (const uint4*)(g_ring + (((qe.x >> 24) & 0x7f) * (PV * 8192) + vlane + (((qe.x >> (o >> 1)) & 1) << 12)));
            const uint32_t* xp = (const uint32_t*)(g_ring + (ab + xlane + ((qe.x >> 2) & 0x1000)));
            const uint32_t* cp = (const uint32_t*)(g_ring + (ab + clane + ((qe.x >> 3) & 0x1000)));
            uint4 v[STEPS]; uint32_t x[STEPS];
            const uint32_t cn = __ldcg(cp);
#pragma unroll
            for (int j = 0; j < STEPS; j++) x[j] = __ldcg(xp + j * 32);
#pragma unroll
            for (int j = 0; j < STEPS; j++) v[j] = ld128(vp + j * 32);
            for (int spins = 0;; spins++) {
                uint32_t bad = 0;
#pragma unroll
                for (int j = 0; j < STEPS; j++) bad |= v[j].x ^ tag;
                if (!__any_sync(0xffffffffu, bad & 1)) break;
                if (spins > (1 << 22)) __trap();
#pragma unroll
                for (int j = 0; j < STEPS; j++) v[j] = ld128(vp + j * 32);
            }
            uint32_t ad[2 * STEPS], dep = cn;
#pragma unroll
            for (int j = 0; j < STEPS; j++) {
                const uint32_t c = (cn >> (8 * j)) & 0xff;
                ad[2 * j] = r0 < c ? sb + (x[j] & 0xffff) * 8 : dummy;
                ad[2 * j + 1] = r0 + 1 < c ? sb + (x[j] >> 16) * 8 : dummy;
                dep ^= x[j];
            }
            if (lane == 0) asm volatile("red.relaxed.gpu.global.add.u32 [%0],%1;" ::"l"(fb + (qe.y & 63) * 4 + (((qe.y >> 6) + DV) & 3)), "r"(1 + (dep & p.zero)) : "memory");
            uint32_t pend = 0;
#pragma unroll
            for (int j0 = 0; j0 < 2 * STEPS; j0 += 4) {
                uint2 t[4];
#pragma unroll
                for (int j = 0; j < 4; j++) t[j] = lock64(ad[j0 + j]);
#pragma unroll
                for (int j = 0; j < 4; j++) {
                    const int jj = j0 + j;
                    const uint32_t vx = (jj & 1) ? v[jj / 2].z : v[jj / 2].x, vy = (jj & 1) ? v[jj / 2].w : v[jj / 2].y;
                    asm volatile("{.reg .pred p,q; setp.ne.u32 p,%4,0xffffffff; @p st.shared.v2.u32 [%1],{%2,%3}; setp.ne.and.u32 q,%1,%5,!p; @q or.b32 %0,%0,%6;}"
                                 : "+r"(pend) : "r"(ad[jj]), "r"(hadd2(t[j].x, vx)), "r"(hadd2(t[j].y, vy)), "r"(t[j].x), "r"(dummy), "r"(1u << jj) : "memory");
                }
            }
            while (__any_sync(0xffffffffu, pend)) {
                uint32_t a = dummy, vx = 0, vy = 0;
#pragma unroll
                for (int jj = 2 * STEPS - 1; jj >= 0; jj--)
                    if (pend & (1u << jj)) { a = ad[jj]; vx = (jj & 1) ? v[jj / 2].z : v[jj / 2].x; vy = (jj & 1) ? v[jj / 2].w : v[jj / 2].y; }
                const uint2 t = lock64(a);
                asm volatile("{.reg .pred p; setp.ne.u32 p,%4,0xffffffff; @p st.shared.v2.u32 [%1],{%2,%3}; @p and.b32 %0,%0,%5;}"
                             : "+r"(pend) : "r"(a), "r"(hadd2(t.x, vx)), "r"(hadd2(t.y, vy)), "r"(t.x), "r"(pend - 1) : "memory");
            }
        }
    }
    asm volatile("fence.proxy.async.shared::cta;" ::: "memory");
    __syncthreads();
    constexpr int CH = 8192;
    if (lane == 0 && warp * CH < (int)SO * 8) {
        asm volatile("fence.proxy.async.global;" ::: "memory");
        const int bytes = min(CH, (int)SO * 8 - warp * CH);
        if (g) asm volatile("cp.async.bulk.global.shared::cta.bulk_group [%0],[%1],%2;" ::"l"((char*)(g_rep + o * SO) + warp * CH), "r"(sb + warp * CH), "r"(bytes) : "memory");
        else asm volatile("cp.reduce.async.bulk.global.shared::cta.bulk_group.add.noftz.bf16 [%0],[%1],%2;" ::"l"((char*)(g_agg + o * SO) + warp * CH), "r"(sb + warp * CH), "r"(bytes) : "memory");
        asm volatile("cp.async.bulk.commit_group;" ::: "memory");
    }
}

__device__ __forceinline__ void mma_edge(float (&c)[4], uint32_t p01, uint32_t q01, uint32_t p23, uint32_t q23, uint2 b) {
    asm("mma.sync.aligned.m16n8k16.row.col.f32.bf16.bf16.f32 {%0,%1,%2,%3},{%4,%5,%6,%7},{%8,%9},{%0,%1,%2,%3};"
        : "+f"(c[0]), "+f"(c[1]), "+f"(c[2]), "+f"(c[3]) : "r"(p01), "r"(q01), "r"(p23), "r"(q23), "r"(b.x), "r"(b.y));
}
__device__ __forceinline__ uint2 b_frag(const uint16_t* w, int j0) {
    const int lane = threadIdx.x & 31, j = j0 + ((lane >> 2) & 1);
    const uint2 v = make_uint2(w[j] | ((uint32_t)w[4 + j] << 16), w[8 + j] | ((uint32_t)w[12 + j] << 16));
    return (lane & 3) == (lane >> 3) ? v : make_uint2(0, 0);
}
__device__ __forceinline__ void edge_gates(const uint16_t* w, uint32_t d2, uint4& sp, uint4& gp) {
    uint32_t rb[2][4];
#pragma unroll
    for (int k = 0; k < 2; k++)
#pragma unroll
        for (int r = 0; r < 4; r++) {
            uint32_t x; asm("sub.rn.bf16x2 %0,%1,%2;" : "=r"(x) : "r"(__byte_perm(d2, 0, k ? 0x3232 : 0x1010)), "r"(((const uint32_t*)w)[48 + r]));
            const uint32_t t = hmul2(hmul2(x, x), 0xc120c120u);
            rb[k][r] = pack2(__expf(bf_lo(t)), __expf(bf_hi(t)));
        }
    uint32_t o[4][2];
#pragma unroll
    for (int n = 0; n < 4; n++) {
        float c[4] = {};
        mma_edge(c, rb[0][0], rb[1][0], rb[0][1], rb[1][1], b_frag(w + (n >> 1) * 32, (n & 1) * 2));
        mma_edge(c, rb[0][2], rb[1][2], rb[0][3], rb[1][3], b_frag(w + (n >> 1) * 32 + 16, (n & 1) * 2));
        o[n][0] = pack2(c[0], c[1]); o[n][1] = pack2(c[2], c[3]);
    }
    gp = make_uint4(o[0][0], o[1][0], o[0][1], o[1][1]);
    sp = make_uint4(o[2][0], o[3][0], o[2][1], o[3][1]);
}
__device__ __forceinline__ uint4 edge_finish(const uint16_t* w, uint4 a, uint4 a2, uint4 sp, uint4 gp, uint4 mv) {
    float t0[4] = {}, t1[4] = {}, u0[4] = {}, u1[4] = {};
    mma_edge(t0, a.x, a.z, a.y, a.w, b_frag(w + 64, 0));
    mma_edge(t1, a.x, a.z, a.y, a.w, b_frag(w + 64, 2));
    mma_edge(t0, a2.x, a2.z, a2.y, a2.w, b_frag(w + 64, 0));
    mma_edge(t1, a2.x, a2.z, a2.y, a2.w, b_frag(w + 64, 2));
    const uint32_t p01 = pack2(t0[0] * bf_lo(sp.x), t0[1] * bf_hi(sp.x)), p23 = pack2(t1[0] * bf_lo(sp.y), t1[1] * bf_hi(sp.y));
    const uint32_t q01 = pack2(t0[2] * bf_lo(sp.z), t0[3] * bf_hi(sp.z)), q23 = pack2(t1[2] * bf_lo(sp.w), t1[3] * bf_hi(sp.w));
    mma_edge(u0, p01, q01, p23, q23, b_frag(w + 80, 0));
    mma_edge(u1, p01, q01, p23, q23, b_frag(w + 80, 2));
    return make_uint4(hadd2(mv.x, hmul2(pack2(u0[0], u0[1]), gp.x)), hadd2(mv.y, hmul2(pack2(u1[0], u1[1]), gp.y)),
                      hadd2(mv.z, hmul2(pack2(u0[2], u0[3]), gp.z)), hadd2(mv.w, hmul2(pack2(u1[2], u1[3]), gp.w)));
}

__device__ __forceinline__ void finish(const Params& p, unsigned char* sm) {
    __syncwarp();
    const int b = blockIdx.x, tid = threadIdx.x;
    const int role = ((const volatile uint32_t*)(sm + SM_AUX + AUX_MISC))[2];
    const uint16_t* w = (const uint16_t*)(sm + SM_AUX + AUX_W);
    if (role != 3) {
        __syncthreads();
        if (tid == 0) asm volatile("red.release.gpu.global.add.u32 [%0],1;" ::"l"(&g_sync[SY_END]) : "memory");
    }
    constexpr int EP = 3, es = NCTA * 1024;
    static_assert(EP * es * 2 >= E_CAP, "epilogue");
    uint4 sg[2 * EP];
    const int e0 = b * 1024 + tid, np = p.E / 2;
#pragma unroll
    for (int k = 0; k < EP; k++) sg[2 * k].x = __ldg((const uint32_t*)p.dist + min(e0 + k * es, np - 1));
#pragma unroll
    for (int k = 0; k < EP; k++) edge_gates(w, sg[2 * k].x, sg[2 * k], sg[2 * k + 1]);
    uint4 mv[EP];
#pragma unroll
    for (int k = 0; k < EP; k++) mv[k] = __ldg((const uint4*)p.m + min(e0 + k * es, np - 1));
    if (role == 3) {
        asm volatile("cp.async.bulk.wait_group 0;" ::: "memory");
        __syncthreads();
        if (tid == 0) asm volatile("red.release.gpu.global.add.u32 [%0],1;" ::"l"(&g_sync[SY_END]) : "memory");
    }
    uint4* const stash = (uint4*)sm + tid;
#pragma unroll
    for (int k = 0; k < EP; k++) { stash[(3 * k) * 1024] = sg[2 * k]; stash[(3 * k + 1) * 1024] = sg[2 * k + 1]; stash[(3 * k + 2) * 1024] = mv[k]; }
    if (tid == 0) {
        wait_flag(&g_sync[SY_END], NCTA);
        asm volatile("fence.acquire.gpu;" ::: "memory");
    }
    __syncthreads();
    uint4 av[EP], aw[EP];
#pragma unroll
    for (int k = 0; k < EP; k++) {
        const int e = min(e0 + k * es, np - 1);
        av[k] = __ldcg((const uint4*)g_agg + e); aw[k] = __ldcg((const uint4*)g_rep + e);
    }
#pragma unroll
    for (int k = 0; k < EP; k++) {
        const uint4 o = edge_finish(w, av[k], aw[k], stash[(3 * k) * 1024], stash[(3 * k + 1) * 1024], stash[(3 * k + 2) * 1024]);
        if (e0 + k * es < np) ((uint4*)p.out)[e0 + k * es] = o;
    }
    if (b == 0 && tid < 512) ((uint4*)(g_ring + slot_v(KV)))[tid] = make_uint4(0, 0, 0, 0);
    if (tid == 0) {
        g_info[b] = make_uint2(0, 0);
        if (atomicAdd(&g_sync[SY_EXIT], 1) == NCTA - 1)
            g_sync[SY_ZERO] = g_sync[SY_END] = g_sync[SY_EXIT] = g_sync[SY_WORK] = g_sync[SY_LOG] = g_sync[SY_LOG + 1] = 0;
    }
}

__global__ void __launch_bounds__(1024, 1) main_kernel(const __grid_constant__ Params p) {
    extern __shared__ __align__(128) unsigned char sm[];
    const int b = blockIdx.x, tid = threadIdx.x, warp = tid >> 5;
    if ((uint32_t)__cvta_generic_to_shared(sm) != SB) __trap();
    uint32_t* s_misc = (uint32_t*)(sm + SM_AUX + AUX_MISC);
    if (tid == 0) s_misc[0] = s_misc[4] = s_misc[5] = 0;
    __syncthreads();
    if ((tid & 31) == 0) {
        const int sl = b * 2 + (warp >> 4), j = warp & 15;
        if (warp == 31) s_misc[1] = upper_is_near(g_probe + (b & 127) * 32);
        else if (sl < NSL && j < (sl < KA ? PA : sl < KA + KV ? PV : 1) &&
                 upper_is_near(g_ring + (sl < KA ? slot_a(sl) : slot_v(sl - KA)) + j * 8192 + 4064))
            atomicOr(&s_misc[0], 1u << warp);
    }
    __syncwarp();
    __syncthreads();
    uint32_t me; asm("mov.u32 %0,%%smid;" : "=r"(me));
    me = 0x8000u | (s_misc[1] << 14) | (me & 0x3fff);
    if (tid == 0) {
        const u64 v = (u64)(s_misc[0] ^ (s_misc[1] ? ~0u : 0u)) | ((u64)me << 32);
        asm volatile("st.release.gpu.global.u64 [%0],%1;" ::"l"(&g_info[b]), "l"(v) : "memory");
    }
    for (int i = tid; i < (SM_AUX + AUX_CLS) / 16; i += 1024) ((uint4*)sm)[i] = make_uint4(0, 0, 0, 0);
    uint16_t* w = (uint16_t*)(sm + SM_AUX + AUX_W);
    if (tid < 160) {
        u64 v = 0; int spins = 0;
        while (tid < NCTA && !(v >> 32)) {
            asm volatile("ld.acquire.gpu.global.u64 %0,[%1];" : "=l"(v) : "l"(&g_info[tid]) : "memory");
            if (++spins > (1 << 22)) __trap();
        }
        __syncwarp();
        if (tid < NCTA) ((uint32_t*)(sm + SM_AUX + AUX_CLS))[tid] = (uint32_t)v;
        const uint32_t o = v >> 32;
        const uint32_t c = __reduce_add_sync(0xffffffffu, tid < NCTA ? 1u << (8 * ((o & 1) | ((o >> 13) & 2))) : 0u);
        const uint32_t r = __popc(__ballot_sync(0xffffffffu, tid < NCTA && ((o ^ me) & 0x4001) == 0 && (o > me || (o == me && tid > b))));
        if ((tid & 31) == 0) { atomicAdd(&s_misc[4], c); atomicAdd(&s_misc[5], r); }
    } else if (tid >= 256 && tid < 256 + 104) {
        const int j = tid - 256;
        w[j] = j < 32 ? p.w_rbf[j] : j < 64 ? p.w_sbf[j - 32] : j < 80 ? p.w_down[j - 64] : j < 96 ? p.w_up[j - 80] : p.centers[j - 96];
    }
    __syncthreads();
    int role, rank;
    {
        const uint32_t cnt = s_misc[4], cl = (me & 1) | ((me >> 13) & 2);
        rank = s_misc[5];
        const int c2 = (rank + 1) * IG / NO;
        if (__vminu4(cnt, NO * 0x01010101u) != NO * 0x01010101u) {
            role = b < N2 ? 2 : b < N2 + N3 ? 3 : 1;
            const int r = role == 2 ? b : b - N2;
            rank = role == 1 ? b - N2 - N3 : (r >> 1) | ((r & 1) << 8);
        } else if (rank < NO && (me & 1)) { role = 3; rank |= (cl >> 1) << 8; }
        else if (rank < NO && c2 != rank * IG / NO) { role = 2; rank = (c2 - 1) | ((cl >> 1) << 8); }
        else {
            role = 1;
            rank -= (me & 1) ? NO : min(c2, IG);
            for (uint32_t c = 0; c < cl; c++) rank += ((cnt >> (8 * c)) & 0xff) - ((c & 1) ? NO : IG);
        }
        if (tid == 0) s_misc[2] = role;
    }
    if (role == 1) stage1(p, sm, rank);
    else if (role == 2) stage2(p, sm, rank >> 8, rank & 255);
    else stage3(p, sm, rank >> 8, rank & 255);
    finish(p, sm);
}

__global__ void generic_scatter(const __grid_constant__ Params p) {
    const float f = bf_lo(p.freq[0]);
    for (int t = blockIdx.x * blockDim.x + threadIdx.x; t < p.T; t += gridDim.x * blockDim.x) {
        const uint2 v = __ldg(p.m + p.idx_in[t]);
        const uint32_t c2 = dup_bf16(cos_any(rbf16(f * bf_lo(p.angle[t]))));
        asm volatile("red.global.add.noftz.v2.bf16x2 [%0],{%1,%2};" ::"l"(p.out + p.idx_out[t]), "r"(hmul2(v.x, c2)), "r"(hmul2(v.y, c2)) : "memory");
    }
}
__global__ void __launch_bounds__(256) generic_finish(const __grid_constant__ Params p) {
    __shared__ __align__(16) uint16_t w[104];
    const int j = threadIdx.x, e = blockIdx.x * blockDim.x + j, ec = min(e, p.E - 1);
    if (j < 104) w[j] = j < 32 ? p.w_rbf[j] : j < 64 ? p.w_sbf[j - 32] : j < 80 ? p.w_down[j - 64] : j < 96 ? p.w_up[j - 80] : p.centers[j - 96];
    const uint2 a = p.out[ec], mv = p.m[ec];
    __syncthreads();
    uint4 s0, s1;
    edge_gates(w, p.dist[ec] * 0x10001u, s0, s1);
    const uint4 o = edge_finish(w, make_uint4(a.x, a.y, a.x, a.y), make_uint4(0, 0, 0, 0), s0, s1, make_uint4(mv.x, mv.y, mv.x, mv.y));
    if (e < p.E) p.out[e] = make_uint2(o.x, o.y);
}

extern "C" void kernel_launch(void* const* d_in, const int* in_sizes, int n_in, void* d_out, int out_size) {
    static int nsm = 0;
    if (!nsm) {
        cudaDeviceGetAttribute(&nsm, cudaDevAttrMultiProcessorCount, 0);
        cudaFuncSetAttribute(main_kernel, cudaFuncAttributeMaxDynamicSharedMemorySize, SMEM_BYTES);
    }
    Params p;
    p.m = (const uint2*)d_in[0]; p.idx_in = (const int*)d_in[1]; p.idx_out = (const int*)d_in[2];
    p.angle = (const uint16_t*)d_in[4]; p.freq = (const uint16_t*)d_in[6];
    p.dist = (const uint16_t*)d_in[3]; p.centers = (const uint16_t*)d_in[5]; p.w_rbf = (const uint16_t*)d_in[7];
    p.w_sbf = (const uint16_t*)d_in[8]; p.w_down = (const uint16_t*)d_in[9]; p.w_up = (const uint16_t*)d_in[10];
    p.out = (uint2*)d_out;
    p.E = in_sizes[3]; p.T = in_sizes[1];
    p.zero = 0;
    p.pairs = p.T / (2 * STEP); p.units = p.pairs + (NR / 2 + 1) * N1;
    bool fast = nsm >= NCTA && p.E <= E_CAP && p.E >= 8 && p.E % 2 == 0 && p.pairs >= 2 * N1 && p.units < 0xff00;
    static cudaTextureObject_t tex[3];
    static const void* tex_ptr[3];
    static int tex_n[3];
    for (int k = 0; k < 3 && fast; k++) {
        void* ptr = d_in[k == 2 ? 4 : 1 + k];
        if (tex_ptr[k] == ptr && tex_n[k] == p.T) continue;
        cudaResourceDesc rd = {};
        rd.resType = cudaResourceTypeLinear;
        rd.res.linear.devPtr = ptr;
        rd.res.linear.desc = k == 2 ? cudaCreateChannelDesc<uint2>() : cudaCreateChannelDesc<uint4>();
        rd.res.linear.sizeInBytes = (size_t)(p.T / 4) * (k == 2 ? 8 : 16);
        cudaTextureDesc td = {};
        td.readMode = cudaReadModeElementType;
        if (cudaCreateTextureObject(&tex[k], &rd, &td, nullptr) == cudaSuccess) { tex_ptr[k] = ptr; tex_n[k] = p.T; }
        else { cudaGetLastError(); tex_ptr[k] = nullptr; fast = false; }
    }
    p.tin = tex[0]; p.tout = tex[1]; p.tang = tex[2];
    if (!fast) {
        cudaMemsetAsync(d_out, 0, (size_t)p.E * 8);
        generic_scatter<<<nsm * 8, 256>>>(p);
        generic_finish<<<(p.E + 255) / 256, 256>>>(p);
        return;
    }
    void* args[] = {&p};
    cudaLaunchCooperativeKernel((const void*)main_kernel, dim3(NCTA), dim3(1024), args, SMEM_BYTES, cudaStreamPerThread);
}
```

```cpp
#include <cuda_runtime.h>
#include <cuda_bf16.h>
#include <stdint.h>

typedef unsigned long long u64;
constexpr uint32_t magic_of(uint32_t d) { return (uint32_t)(((1ull << 32) + d - 1) / d); }
constexpr uint32_t slice_of(uint32_t total, uint32_t n) {
    uint32_t d = ((total + n - 1) / n + 1) & ~1u;
    while (!((uint64_t)(n * d - 1) * magic_of(d) < ((uint64_t)n << 32))) d += 2;
    return d;
}
constexpr int E_CAP = 800000;
constexpr int NI = 32, NO = 28, NG = 2, IG = NI / NG;
constexpr uint32_t SI = slice_of(E_CAP, NI), SO = slice_of(E_CAP, NO);
constexpr uint32_t MI = magic_of(SI), MO = magic_of(SO);
constexpr int NCTA = 132, N2 = NI, N3 = NO * NG, N1 = NCTA - N2 - N3;
constexpr int C = 16, GB = NO * IG;
constexpr int NP = 5;
constexpr int NW = 28, STEP = NW * 256;
constexpr int NR = 4, LOGCAP = 8192, NCH = N1 * NW * NR * 8, KMAX = 4000;
static_assert(NR % 2 == 0 && NR >= 2 && NR <= 4 && NO % 4 == 0 && IG == 16, "shape");

constexpr int DA = 3, DS = 2, DV = 2, KA = DA * N1, KV = DV * N1, NSL = KA + KV + 1;
constexpr int ASEG = NO * C * 4, XSEG = IG * C * 2, VSEG = IG * C * 8;
constexpr int AG = IG * ASEG, XG = NO * XSEG, XO = IG / 2 * 4096, AXG = XO + XG + GB;
constexpr int PA = (AXG + 4095) / 4096, PV = NO * VSEG / 4096;
static_assert(2 * ASEG <= 4096 && AG == 2 * XG && (XO + XG) / 4096 == (AXG - 1) / 4096 && PA <= 15 && PV <= 14, "layout");
static_assert(DS >= DA - DV && DS <= DA && KA <= 256 && KV <= 128 && NSL <= 2 * NCTA && N1 <= 64, "ring");

constexpr uint32_t SB = 1024;
constexpr int SM_CNT = 0, SM_CB = NG * GB * 4, SM_LC = SM_CB + 2 * GB, SM_X = SM_LC + 256, SM_A = SM_X + NP * XG,
              SM_S1_END = SM_A + NP * AG;
constexpr int SM_AUX = SO * 8 + 512, QN = 256;
constexpr int AUX_Q = 0, AUX_PROG = QN * 8, AUX_CLS = AUX_PROG + 128, AUX_MISC = AUX_CLS + 576, AUX_DUMMY = AUX_MISC + 32,
              AUX_W = AUX_DUMMY + 256, AUX_END = AUX_W + 208;
constexpr int SMEM_BYTES = SM_AUX + AUX_END;
static_assert(SM_S1_END + 256 <= SM_AUX && SMEM_BYTES <= 232448 && SM_X % 128 == 0 && AUX_W % 16 == 0, "smem");

__device__ __align__(8192) unsigned char g_ring[(size_t)(KA * PA + KV * PV + 1) * 8192];
__device__ __align__(8192) unsigned char g_probe[8192];
__device__ uint2 g_log[N1 * NW * LOGCAP];
__device__ uint32_t g_chunks[NCH];
__device__ __align__(128) uint2 g_agg[NO * SO];
__device__ __align__(128) uint2 g_rep[NO * SO];
__device__ uint2 g_info[NCTA];
__device__ __align__(128) uint32_t g_sync[160];
constexpr int SY_ZERO = 0, SY_END = 32, SY_EXIT = 64, SY_WORK = 96, SY_LOG = 128;
constexpr int FL_GO2 = 0, FL_GO3 = 1;
constexpr uint32_t FL_DATA = 0x10000;

__device__ __forceinline__ int lane_id() { int v; asm volatile("mov.u32 %0,%%laneid;" : "=r"(v)); return v; }
__device__ __forceinline__ int warp_id() { int v; asm volatile("mov.u32 %0,%%tid.x;" : "=r"(v)); return __shfl_sync(0xffffffffu, v >> 5, 0); }
__device__ __forceinline__ float bf_lo(uint32_t v) { return __uint_as_float(v << 16); }
__device__ __forceinline__ float bf_hi(uint32_t v) { return __uint_as_float(v & 0xffff0000u); }
__device__ __forceinline__ float rbf16(float x) { return __bfloat162float(__float2bfloat16_rn(x)); }
__device__ __forceinline__ uint32_t hmul2(uint32_t a, uint32_t b) {
    uint32_t d; asm("mul.rn.bf16x2 %0,%1,%2;" : "=r"(d) : "r"(a), "r"(b)); return d;
}
__device__ __forceinline__ uint32_t hadd2(uint32_t a, uint32_t b) {
    uint32_t d; asm("add.rn.bf16x2 %0,%1,%2;" : "=r"(d) : "r"(a), "r"(b)); return d;
}
__device__ __forceinline__ uint32_t dup_bf16(float x) {
    uint32_t d; asm("cvt.rn.bf16x2.f32 %0,%1,%1;" : "=r"(d) : "f"(x)); return d;
}
__device__ __forceinline__ uint32_t pack2(float lo, float hi) {
    uint32_t d; asm("cvt.rn.bf16x2.f32 %0,%2,%1;" : "=r"(d) : "f"(lo), "f"(hi)); return d;
}
__device__ __noinline__ float cos_slow(float x) { return cosf(x); }
__device__ __forceinline__ float cos_any(float x) { return fabsf(x) < 32.f ? __cosf(x) : cos_slow(x); }
__device__ __forceinline__ void bar_sync(int id, int n) { asm volatile("barrier.sync.aligned %0,%1;" ::"r"(id), "r"(n) : "memory"); }
__device__ __forceinline__ void bar_arrive(int id, int n) { asm volatile("barrier.arrive.aligned %0,%1;" ::"r"(id), "r"(n) : "memory"); }
__device__ __forceinline__ uint32_t ld_relaxed(const uint32_t* p) {
    uint32_t v; asm volatile("ld.relaxed.gpu.global.u32 %0,[%1];" : "=r"(v) : "l"(p) : "memory"); return v;
}
__device__ __forceinline__ void st128(void* p, uint4 v) {
    asm volatile("{.reg .b64 a,b; .reg .b128 q; mov.b64 a,{%1,%2}; mov.b64 b,{%3,%4}; mov.b128 q,{a,b}; st.relaxed.gpu.global.b128 [%0],q;}" ::"l"(p), "r"(v.x), "r"(v.y), "r"(v.z), "r"(v.w) : "memory");
}
__device__ __forceinline__ uint4 ld128(const void* p) {
    uint4 v;
    asm volatile("{.reg .b64 a,b; .reg .b128 q; ld.relaxed.gpu.global.b128 q,[%4]; mov.b128 {a,b},q; mov.b64 {%0,%1},a; mov.b64 {%2,%3},b;}" : "=r"(v.x), "=r"(v.y), "=r"(v.z), "=r"(v.w) : "l"(p) : "memory");
    return v;
}
__device__ __forceinline__ void wait_flag(const uint32_t* p, uint32_t want) {
    int spins = 0;
    while ((ld_relaxed(p) & 0xffff) < want) {
        __nanosleep(50);
        if (++spins > (1 << 22)) __trap();
    }
}
__device__ __forceinline__ uint32_t slot_a(int s) { return s * (PA * 8192); }
__device__ __forceinline__ uint32_t slot_v(int s) { return KA * PA * 8192 + s * (PV * 8192); }
__device__ __forceinline__ uint32_t ring_off(uint32_t clsg, uint32_t off) {
    return ((off >> 12) << 13) + (((clsg >> (off >> 12)) & 1) << 12) + (off & 4095);
}
__device__ __forceinline__ uint32_t cls_of(const unsigned char* sm, int s, int g) {
    return ((const uint16_t*)(sm + SM_AUX + AUX_CLS))[s] ^ (g ? ~0u : 0u);
}
__device__ __forceinline__ uint32_t* flag_base(const unsigned char* sm, int g, int type) {
    return (uint32_t*)(g_ring + slot_v(KV) + ring_off(cls_of(sm, NSL - 1, g), type * 1024));
}
__device__ __forceinline__ uint32_t arrivals(int type, uint32_t k) {
    return type == FL_GO3 ? IG * ((k >> 2) + 1) : NO * ((k >> 2) + ((k & 3) >= DV));
}
__device__ __forceinline__ bool elect_one() {
    uint32_t r; asm volatile("{.reg .pred p; elect.sync _|p,0xffffffff; selp.u32 %0,1,0,p;}" : "=r"(r)); return r;
}
template <int NCW, int TYPE, class F>
__device__ __forceinline__ void poller(const unsigned char* sm, int g, int blk0, int blk1, int units, int hook_at, F hook) {
    const int lane = lane_id();
    constexpr uint32_t aux = SB + SM_AUX;
    constexpr int DR = TYPE == FL_GO2 ? DS : DA;
    const uint32_t lt = (1u << lane) - 1;
    const uint32_t* const fb = flag_base(sm, g, TYPE) + lane * 4;
    uint32_t ea[2][DR], ev[2][DV], k[2] = {0, 0}, want[2], v[2];
#pragma unroll
    for (int j = 0; j < 2; j++) {
        const int q = min(lane + j * 32, N1 - 1);
#pragma unroll
        for (int d = 0; d < DR; d++) {
            const uint32_t sa = q + d * N1, ca = cls_of(sm, sa, g);
            ea[j][d] = (((ca >> blk0) & 1) << 14) | (((ca >> blk1) & 1) << 15) | (sa << 16);
        }
#pragma unroll
        for (int d = 0; d < DV; d++) ev[j][d] = (cls_of(sm, KA + q + d * N1, g) & 0x3fff) | ((q + d * N1) << 24);
        want[j] = lane + j * 32 < N1 ? FL_DATA + arrivals(TYPE, 0) : ~0u;
        v[j] = 0;
    }
    int tail = 0, check = min(min(QN - N1, hook_at), units), spins = 0;
    while (true) {
        bool hit[2]; uint32_t bal[2];
#pragma unroll
        for (int j = 0; j < 2; j++) {
            hit[j] = v[j] >= want[j];
            bal[j] = __ballot_sync(0xffffffffu, hit[j]);
        }
        if (bal[0] | bal[1]) {
            asm volatile("fence.acquire.gpu;" ::: "memory");
            if (TYPE == FL_GO2) asm volatile("fence.proxy.async.global;" ::: "memory");
            asm volatile("fence.acq_rel.cta;" ::: "memory");
            spins = 0;
        } else if (++spins > (1 << 22)) __trap();
#pragma unroll
        for (int j = 0; j < 2; j++) {
            const uint32_t pos = tail + __popc(bal[j] & lt);
            const uint32_t hi = (lane + j * 32) | ((k[j] & 0xff) << 6) | (k[j] < DV ? 0x4000 : 0) | ((pos + 1) << 16);
            asm volatile("{.reg .pred p; .reg .b64 q; setp.ne.u32 p,%3,0; mov.b64 q,{%1,%2}; @p st.relaxed.cta.shared.u64 [%0],q;}"
                         ::"r"(aux + AUX_Q + (pos % QN) * 8), "r"(ea[j][0] | ev[j][0]), "r"(hi), "r"((uint32_t)hit[j]) : "memory");
            tail += __popc(bal[j]);
            k[j] += hit[j];
        }
#pragma unroll
        for (int j = 0; j < 2; j++) v[j] = ld_relaxed(fb + (j && lane + 32 < N1 ? 128 : 0) + (k[j] & 3));
#pragma unroll
        for (int j = 0; j < 2; j++) {
            const uint32_t a0 = ea[j][0], v0 = ev[j][0] ^ 0x80000000u;
#pragma unroll
            for (int d = 0; d < DR; d++) ea[j][d] = hit[j] ? (d + 1 < DR ? ea[j][(d + 1) % DR] : a0) : ea[j][d];
#pragma unroll
            for (int d = 0; d < DV; d++) ev[j][d] = hit[j] ? (d + 1 < DV ? ev[j][(d + 1) % DV] : v0) : ev[j][d];
            want[j] = hit[j] ? ((k[j] >> 2) + 1) * FL_DATA + arrivals(TYPE, k[j]) : want[j];
        }
        if (tail >= check) {
            if (tail >= units) break;
            if (tail >= hook_at) { hook(); hook_at = 0x7fffffff; }
            int limit;
            do {
                int prog; asm volatile("ld.volatile.shared.u32 %0,[%1];" : "=r"(prog) : "r"(aux + AUX_PROG + min(lane, NCW - 1) * 4) : "memory");
                limit = __reduce_min_sync(0xffffffffu, prog) + QN - N1;
            } while (tail > limit);
            check = min(min(limit, hook_at), units);
        }
    }
}
template <bool BLOCK>
__device__ __forceinline__ bool next_unit(uint32_t aux, int warp, int t, int step, uint2& e) {
    u64 v;
    while (true) {
        asm volatile("ld.acquire.cta.shared.u64 %0,[%1];" : "=l"(v) : "r"(aux + AUX_Q + (t % QN) * 8) : "memory");
        if (__all_sync(0xffffffffu, (int)(v >> 48) == t + 1)) break;
        if (!BLOCK) return false;
        __nanosleep(40);
    }
    if (((t + step) ^ t) & 64) asm volatile("st.volatile.shared.u32 [%0],%1;" ::"r"(aux + AUX_PROG + warp * 4), "r"(t + step) : "memory");
    e = make_uint2((uint32_t)v, (uint32_t)(v >> 32) & 0xffff);
    return true;
}
__device__ __forceinline__ int upper_is_near(unsigned char* q) {
    ((uint4*)q)[0] = ((uint4*)q)[1] = ((uint4*)(q + 4096))[0] = ((uint4*)(q + 4096))[1] = make_uint4(0, 0, 0, 0);
    uint32_t best[2] = {~0u, ~0u};
#pragma unroll
    for (int r = 0; r < 4; r++) {
        uint32_t t0, t1, v;
        asm volatile("mov.u32 %0,%%clock;" : "=r"(t0)::"memory");
        asm volatile("atom.global.exch.b32 %0,[%1],0;" : "=r"(v) : "l"(q + (r & 1) * 4096) : "memory");
        asm volatile("{.reg .pred p; setp.eq.u32 p,%1,0xffffffff; @p trap; mov.u32 %0,%%clock;}" : "=r"(t1) : "r"(v) : "memory");
        best[r & 1] = min(best[r & 1], t1 - t0);
    }
    return best[1] < best[0];
}

struct Params {
    const uint2* m; const int* idx_in; const int* idx_out; const uint16_t* angle; const uint16_t* freq;
    const uint16_t *dist, *centers, *w_rbf, *w_sbf, *w_down, *w_up; uint2* out;
    int E, T, pairs, units;
    uint32_t zero;
    cudaTextureObject_t tin, tout, tang;
};

__device__ __forceinline__ void red_agg(uint32_t out, uint2 v, uint32_t c2) {
    asm volatile("red.global.add.noftz.v2.bf16x2 [%0],{%1,%2};" ::"l"(g_agg + out), "r"(hmul2(v.x, c2)), "r"(hmul2(v.y, c2)) : "memory");
}
__device__ __forceinline__ void decode_entry(uint32_t e0, uint32_t e1, uint32_t& in, uint32_t& out) {
    const uint32_t bx = e1 >> 21, g = bx >= GB, rem = bx - g * GB;
    in = (g * IG + rem % IG) * SI + (e0 & 0xffff);
    out = rem / IG * SO + (e1 & 0xffff);
}
__device__ __forceinline__ void wait_zeroed() {
    wait_flag(&g_sync[SY_ZERO], N3);
    asm volatile("fence.acquire.gpu;" ::: "memory");
}
constexpr int BAR_ATOMS = 1, BAR_STS = 2, BAR_PUB = 4, BAR_PUBFREE = 6, BAR_W = 8;
constexpr int NT_STS = (NW + 2) * 32, NT_ATOMS = (NW + 1) * 32;
__device__ __forceinline__ void mbar_arrive(uint32_t bar) {
    __syncwarp();
    if (elect_one()) asm volatile("mbarrier.arrive.shared::cta.b64 _,[%0];" ::"r"(bar) : "memory");
}
__device__ __forceinline__ void mbar_wait(uint32_t bar, uint32_t parity) {
    asm volatile("{.reg .pred p; .reg .u32 n; mbarrier.try_wait.parity.shared::cta.b64 p,[%0],%1; @p bra D; mov.u32 n,0;\n"
                 "W: mbarrier.try_wait.parity.shared::cta.b64 p,[%0],%1,2000; @p bra D;\n"
                 "add.u32 n,n,1; setp.lt.u32 p,n,0x4000000; @p bra W; trap;\nD:}" ::"r"(bar), "r"(parity) : "memory");
}
__device__ __forceinline__ uint32_t mad(uint32_t a, uint32_t b, uint32_t c) {
    uint32_t d; asm("mad.lo.u32 %0,%1,%2,%3;" : "=r"(d) : "r"(a), "r"(b), "r"(c)); return d;
}
template <bool R, int G> struct Kind { static constexpr bool replay = R; static constexpr int group = G; };

__device__ __forceinline__ void stage1(const Params& p, unsigned char* sm, int pid) {
    const int warp = warp_id(), lane = lane_id();
    constexpr uint32_t sb = SB;
    uint4 ra[2], rb[2]; uint2 rc[2];
    volatile int* const s_next = (volatile int*)(sm + SM_LC + 64);
    const int total = p.pairs * 2;
    constexpr uint32_t mb = sb + SM_LC;
    if (threadIdx.x < 4) asm volatile("mbarrier.init.shared::cta.b64 [%0],1;" ::"r"(mb + threadIdx.x * 8) : "memory");
    if (threadIdx.x == 0) s_next[2] = 0x7ffffff0;
    if (threadIdx.x < 32) s_next[16 + threadIdx.x] = 2 * C;
    __syncthreads();
    if (warp < NW) {
        constexpr uint32_t cb = sb + SM_CNT, xdum = (uint32_t)(SM_LC + 128 - SM_CNT) << 19;
        constexpr uint32_t xk = sb + SM_X, ak = sb + SM_A - 2 * xk;
        uint32_t cur0 = xk + (lane & p.zero), nxt0 = cur0 + 2 * XG - C * 2, cur1 = cur0, nxt1 = nxt0;
        uint32_t fresh = cur0 + 4 * XG - C * 2, n0 = 0, wpos = 0, chunk = 0;
        int h_in = pid * 2, np = 0;
        uint2* const log = g_log + (pid * NW + warp) * LOGCAP;
        const uint32_t ltmask = ((1u << lane) - 1) | p.zero, tq = threadIdx.x | p.zero;
        auto load_in = [&](int h) {
            const int q = h_in * (STEP / 4) + tq + h * NW * 32;
            asm volatile("tex.1d.v4.u32.s32 {%0,%1,%2,%3},[%4,{%5}];" : "=r"(ra[h].x), "=r"(ra[h].y), "=r"(ra[h].z), "=r"(ra[h].w) : "l"(p.tin), "r"(q));
            asm volatile("tex.1d.v4.u32.s32 {%0,%1,%2,%3},[%4,{%5}];" : "=r"(rb[h].x), "=r"(rb[h].y), "=r"(rb[h].z), "=r"(rb[h].w) : "l"(p.tout), "r"(q));
            asm volatile("{.reg .b32 z,w; tex.1d.v4.u32.s32 {%0,%1,z,w},[%2,{%3}];}" : "=r"(rc[h].x), "=r"(rc[h].y) : "l"(p.tang), "r"(q));
        };
        auto direct = [&](uint32_t first, uint32_t stride, uint32_t count, auto range) {
            wait_zeroed();
            __syncwarp();
            const float f = bf_lo(p.freq[0]);
            for (uint32_t c0 = first; c0 < count; c0 += stride * 4) {
                uint2 e[4], v[4]; uint32_t ok = 0, big = 0;
#pragma unroll
                for (int k = 0; k < 4; k++) {
                    uint32_t lo, hi;
                    range(min(c0 + k * stride, count - 1), lo, hi);
                    e[k] = __ldcg(g_log + min(lo + lane, hi - 1));
                    if (lo + lane < hi && c0 + k * stride < count) ok |= 1u << k;
                }
#pragma unroll
                for (int k = 0; k < 4; k++) {
                    uint32_t in;
                    decode_entry(e[k].x, e[k].y, in, e[k].y);
                    v[k] = __ldg(p.m + in);
                    e[k].x = __float_as_uint(rbf16(f * bf_hi(e[k].x)));
                    big = max(big, e[k].x & 0x7fffffffu);
                }
                const bool slow = __any_sync(0xffffffffu, big >= 0x42000000u);
#pragma unroll
                for (int k = 0; k < 4; k++) {
                    float c = __cosf(__uint_as_float(e[k].x));
                    if (slow) c = cos_slow(__uint_as_float(e[k].x));
                    if ((ok >> k) & 1) red_agg(e[k].y, v[k], dup_bf16(c));
                }
                __syncwarp();
            }
        };
        auto drain = [&]() {
            const uint32_t lb = (pid * NW + warp) * LOGCAP;
            direct(0, 1, (wpos - n0 + 31) / 32, [&](uint32_t c, uint32_t& lo, uint32_t& hi) { lo = lb + n0 + c * 32; hi = lb + wpos; });
            wpos = n0;
        };
        auto load_log = [&](int j) {
            uint2 e[8];
#pragma unroll
            for (int k = 0; k < 8; k++) {
                const uint32_t ch = __shfl_sync(0xffffffffu, chunk, k * NR + j);
                e[k] = make_uint2(0, xdum + (lane << 21));
                if (j < NR && lane < (ch >> 24)) e[k] = __ldcg(g_log + (ch & 0xffffff) * 32 + lane);
            }
#pragma unroll
            for (int h = 0; h < 2; h++) {
                ra[h] = make_uint4(e[h * 4].x, e[h * 4].y, e[h * 4 + 1].x, e[h * 4 + 1].y);
                rb[h] = make_uint4(e[h * 4 + 2].x, e[h * 4 + 2].y, e[h * 4 + 3].x, e[h * 4 + 3].y);
            }
        };
        auto step = [&](const int k2, auto kind) {
            constexpr bool R = decltype(kind)::replay;
            constexpr int G = decltype(kind)::group;
            uint32_t pa[8], aw[8], xw[8], r[8];
#pragma unroll
            for (int h = 0; h < 2; h++) {
                if (!R) {
                    const uint32_t in[4] = {ra[h].x, ra[h].y, ra[h].z, ra[h].w}, out[4] = {rb[h].x, rb[h].y, rb[h].z, rb[h].w};
#pragma unroll
                    for (int k = 0; k < 4; k++) {
                        const uint32_t i = __umulhi(in[k], MI), o = __umulhi(out[k], MO);
                        aw[h * 4 + k] = __byte_perm(in[k] - i * SI, k < 2 ? rc[h].x : rc[h].y, (k & 1) ? 0x7610 : 0x5410);
                        pa[h * 4 + k] = mad(i, NO, o);
                        xw[h * 4 + k] = mad(i, 1u << 21, mad(o, (IG << 21) - SO, out[k]));
                        asm("{.reg .pred p; setp.ge.u32 p,%1,%2; @p add.u32 %0,%0,%3;}" : "+r"(xw[h * 4 + k]) : "r"(in[k]), "n"(IG * SI), "n"((GB - IG) << 21));
                    }
                } else {
#pragma unroll
                    for (int k = h * 4; k < h * 4 + 4; k++) {
                        const uint4 q4 = (k & 2) ? rb[h] : ra[h];
                        const uint2 e = (k & 1) ? make_uint2(q4.z, q4.w) : make_uint2(q4.x, q4.y);
                        aw[k] = e.x; xw[k] = e.y;
                        pa[k] = mad((e.y >> 21) % IG, NO, (e.y >> 25) + (e.y >= GB << 21 ? GB - NO : 0));
                    }
                }
                if (h == 0) {
                    mbar_wait(mb + G * 8, k2 & 1);
                    if (!R) {
                        if (G) asm volatile("ld.volatile.shared.u32 %0,[%1];" : "=r"(h_in) : "r"(mb + 64) : "memory");
                        else h_in++;
                    }
                }
#pragma unroll
                for (int k = h * 4; k < h * 4 + 4; k++)
                    asm volatile("atom.shared.add.u32 %0,[%1+%2],1;" : "=r"(r[k]) : "r"(xw[k] >> 19), "n"(cb) : "memory");
            }
            bar_arrive(BAR_ATOMS, NT_ATOMS);
            mbar_wait(mb + 16 + G * 8, k2 & 1);
            if (!R) {
                load_in(0);
                if (p.zero) __nanosleep(0);
            }
            uint32_t ovf = 0;
#pragma unroll
            for (int k = 0; k < 8; k++) {
                const bool lo = r[k] < C, hi = xw[k] >= GB << 21;
                const uint32_t s2 = r[k] * 2 + (hi ? (lo ? cur1 : nxt1) : (lo ? cur0 : nxt0));
                asm volatile("{.reg .pred p; .reg .b16 a,b; setp.lt.u32 p,%5,%6; mov.b32 {a,b},%4;"
                             " @p st.shared.u32 [%1+%8],%2; @p st.shared.u16 [%3],a; @!p or.b32 %0,%0,%7;}"
                             : "+r"(ovf) : "r"(mad(pa[k], C * 2, s2) * 2), "r"(aw[k]), "r"((xw[k] >> 16) + s2), "r"(xw[k]), "r"(r[k]),
                               "n"(2 * C), "r"(R && xw[k] >= xdum ? 0u : 1u << k), "n"(ak) : "memory");
            }
            bar_arrive(BAR_STS + G, NT_STS);
            if (!R) {
                if (p.zero) __nanosleep(0);
                load_in(1);
            }
            uint32_t bal = __ballot_sync(0xffffffffu, ovf != 0);
            while (bal) {
                uint32_t e0 = aw[7], e1 = xw[7];
#pragma unroll
                for (int k = 6; k >= 0; k--)
                    if (ovf & (1u << k)) { e0 = aw[k]; e1 = xw[k]; }
                asm volatile("{.reg .pred p; setp.ne.u32 p,%3,0; @p st.global.v2.u32 [%0],{%1,%2};}" ::"l"(log + (wpos + __popc(bal & ltmask))), "r"(e0), "r"(e1), "r"(ovf) : "memory");
                wpos += __popc(bal);
                ovf &= ovf - 1;
                bal = __ballot_sync(0xffffffffu, ovf != 0);
            }
            if (R) load_log((k2 - np) * 2 + G + 1);
            if (G) { cur1 = nxt1 + C * 2; nxt1 = fresh - XG; }
            else if (!R || k2 != np + NR / 2 - 1) { cur0 = nxt0 + C * 2; nxt0 = fresh; }
            fresh += fresh == xk + (NP - 1) * XG - C * 2 ? -(NP - 1) * XG : XG;
        };
        u64* const logsync = (u64*)&g_sync[SY_LOG];
        for (int stop = total - 2 * 2 * N1; h_in < total;) {
            load_in(0); load_in(1);
            do {
                step(np, Kind<false, 0>());
                step(np, Kind<false, 1>());
                np++;
            } while (h_in < stop && wpos <= LOGCAP - 512);
            if (wpos > LOGCAP - 512) drain();
            if (h_in >= stop && stop < total) {
                const uint32_t nch = min((wpos + 31) / 32, (LOGCAP - 256 * NR) / 32);
                uint32_t base = 0;
                if (lane == 0) base = (uint32_t)atomicAdd(logsync, (u64)nch);
                base = __shfl_sync(0xffffffffu, base, 0);
                const uint32_t mine = min(nch, NCH - min(base, NCH));
                for (uint32_t c = lane; c < mine; c += 32)
                    g_chunks[base + c] = ((pid * NW + warp) * (LOGCAP / 32) + c) | (min(wpos - c * 32, 32u) << 24);
                n0 = min(wpos, mine * 32);
                __syncwarp();
                if (elect_one()) {
                    asm volatile("red.release.gpu.global.add.u64 [%0],%1;" ::"l"(logsync), "l"(1ull << 32) : "memory");
                    if (n0 >= 2) asm volatile("cp.async.bulk.prefetch.L2.global [%0],%1;" ::"l"(log), "r"(n0 / 2 * 16) : "memory");
                }
                __syncwarp();
                stop = total;
            }
        }
        {
            u64 v; int spins = 0;
            do {
                asm volatile("ld.acquire.gpu.global.u64 %0,[%1];" : "=l"(v) : "l"(logsync) : "memory");
                if (++spins > (1 << 22)) __trap();
            } while ((v >> 32) < N1 * NW);
            const uint32_t idx = (((lane / NR) * NW + warp) * NR + lane % NR) * N1 + pid;
            if (lane < 8 * NR && idx < (uint32_t)v) chunk = __ldcg(g_chunks + idx);
            __syncwarp();
        }
        if (wpos > LOGCAP - 256 * NR) drain();
        load_log(0);
#pragma unroll 1
        for (int k2 = np; k2 < np + NR / 2; k2++) {
            step(k2, Kind<true, 0>());
            step(k2, Kind<true, 1>());
        }
        for (int g = 0; g < NG; g++) {
            mbar_wait(mb + g * 8, (np + NR / 2) & 1);
            mbar_wait(mb + 16 + g * 8, (np + NR / 2) & 1);
            bar_arrive(BAR_ATOMS, NT_ATOMS);
            bar_arrive(BAR_STS + g, NT_STS);
        }
        uint2* const rng = (uint2*)(sm + SM_S1_END);
        if (lane == 0) rng[warp] = make_uint2(n0, wpos);
        bar_sync(BAR_W, (NW + 1) * 32);
        const uint2 mine = lane < NW ? rng[lane] : make_uint2(0, 0);
        const uint32_t nch = (mine.y - mine.x + 31) / 32;
        uint32_t end = nch;
#pragma unroll
        for (int d = 1; d < 32; d *= 2) {
            const uint32_t t = __shfl_up_sync(0xffffffffu, end, d);
            if (lane >= d) end += t;
        }
        direct(warp, NW, __shfl_sync(0xffffffffu, end, 31), [&](uint32_t c, uint32_t& lo, uint32_t& hi) {
            const int w = __popc(__ballot_sync(0xffffffffu, end <= c));
            const uint32_t lb = (pid * NW + w) * LOGCAP;
            lo = lb + __shfl_sync(0xffffffffu, mine.x + (c - (end - nch)) * 32, w);
            hi = lb + __shfl_sync(0xffffffffu, mine.y, w);
        });
    } else if (warp == NW) {
        const int row = min(lane, NO - 1), swz = (row >> 1) & 3;
        mbar_arrive(mb);
        int pn = N1 + pid, pnn = 0, nc = 0x7ffffff0;
        for (int s = 0; s < nc; s++) {
            const int hn = min(pn * 2 + (s & 1), total);
            if (hn == total) nc = min(nc, s + 2 + NR + 2);
            const uint32_t sub = s == nc - 4 ? 0 : C, bias = s == nc - 2 ? C : 0;
            uint4* cp = (uint4*)(sm + SM_CNT + (s & 1) * GB * 4) + row * 4;
            bar_sync(BAR_ATOMS, NT_ATOMS);
            uint4 c[4];
#pragma unroll
            for (int j = 0; j < 4; j++) c[j] = cp[j ^ swz];
            __syncwarp();
#pragma unroll
            for (int j = 0; j < 4; j++)
                cp[j ^ swz] = make_uint4(min(max(c[j].x, C), 2 * C) - sub, min(max(c[j].y, C), 2 * C) - sub,
                                         min(max(c[j].z, C), 2 * C) - sub, min(max(c[j].w, C), 2 * C) - sub);
            if (lane == 0 && !(s & 1)) { s_next[0] = hn; s_next[2] = nc; }
            mbar_arrive(mb + ((s + 1) & 1) * 8);
            uint4 w = make_uint4(0, 0, 0, 0);
#pragma unroll
            for (int j = 0; j < 4; j++) {
                const int sh = (j ^ swz) * 8;
                w.x |= min(c[j].x - bias, C) << sh; w.y |= min(c[j].y - bias, C) << sh;
                w.z |= min(c[j].z - bias, C) << sh; w.w |= min(c[j].w - bias, C) << sh;
            }
            mbar_wait(mb + 16 + (s & 1) * 8, (s >> 1) & 1);
            ((uint4*)(sm + SM_CB + (s & 1) * GB))[row] = w;
            asm volatile("fence.proxy.async.shared::cta;" ::: "memory");
            bar_arrive(BAR_STS + (s & 1), NT_STS);
            if (s & 1) pn = min(2 * N1 + __shfl_sync(0xffffffffu, pnn, 0), p.pairs);
            else if (hn < total && s / 2 + 2 < KMAX) {
                if (lane == 0) asm volatile("atom.relaxed.gpu.global.add.u32 %0,[%1],1;" : "=r"(pnn) : "l"(&g_sync[SY_WORK]) : "memory");
            } else pnn = p.pairs;
            const int hp = pn * 2 + ((s & 1) ^ 1);
            if (hp < total && elect_one())
                asm volatile("cp.async.bulk.prefetch.L2.global [%0],%1;" ::"l"(p.angle + hp * STEP), "r"(STEP * 2) : "memory");
            __syncwarp();
        }
    } else if (warp < NW + 3) {
        const int g = warp - NW - 1;
        mbar_arrive(mb + 16 + g * 8);
        const uint32_t* const fb = flag_base(sm, g, lane & 1) + pid * 4;
        for (int s = g; s < s_next[2]; s += 2) {
            const int k = s >> 1, slot = k % DA * N1 + pid, slots = k % DS * N1 + pid, pl = s % NP;
            const uint32_t cls = __shfl_sync(0xffffffffu, cls_of(sm, slot, g), 0), clss = __shfl_sync(0xffffffffu, cls_of(sm, slots, g), 0);
            if (k >= DS) {
                const uint32_t kw = k - ((lane & 1) ? DS : DA - DV);
                wait_flag(fb + (kw & 3), arrivals(lane & 1, kw));
                __syncwarp();
                asm volatile("fence.proxy.async.global;" ::: "memory");
            }
            bar_sync(BAR_STS + g, NT_STS);
            asm volatile("fence.proxy.async.shared::cta;" ::: "memory");
            if (elect_one()) {
                unsigned char* dst = g_ring + slot_a(slot);
#pragma unroll
                for (int j = 0; j < IG / 2; j++)
                    asm volatile("cp.async.bulk.global.shared::cta.bulk_group [%0],[%1],%2;" ::"l"(g_ring + slot_a(slots) + ring_off(clss, j * 4096)),
                                 "r"(sb + SM_A + pl * AG + j * 2 * ASEG), "n"(2 * ASEG) : "memory");
#pragma unroll
                for (int j = 0; j * 4096 < XG; j++)
                    asm volatile("cp.async.bulk.global.shared::cta.bulk_group [%0],[%1],%2;" ::"l"(dst + ring_off(cls, XO + j * 4096)),
                                 "r"(sb + SM_X + pl * XG + j * 4096), "r"(min(4096, XG - j * 4096)) : "memory");
                asm volatile("cp.async.bulk.global.shared::cta.bulk_group [%0],[%1],%2;" ::"l"(dst + ring_off(cls, XO + XG)),
                             "r"(sb + SM_CB + g * GB), "r"(GB) : "memory");
                asm volatile("cp.async.bulk.commit_group;" ::: "memory");
                asm volatile("cp.async.bulk.wait_group 0;" ::: "memory");
            }
            __syncwarp();
            mbar_arrive(mb + 16 + g * 8);
            bar_sync(BAR_PUBFREE + g, 64);
            bar_arrive(BAR_PUB + g, 64);
        }
    } else if (warp == NW + 3) {
        uint32_t* const fb = flag_base(sm, (lane >> 1) & 1, lane & 1) + pid * 4;
        bar_arrive(BAR_PUBFREE, 64);
        bar_arrive(BAR_PUBFREE + 1, 64);
        for (int s = 0; s < s_next[2]; s++) {
            const int g = s & 1;
            bar_sync(BAR_PUB + g, 64);
            if (s + 2 < s_next[2]) bar_arrive(BAR_PUBFREE + g, 64);
            asm volatile("fence.acq_rel.gpu;" ::: "memory");
            if ((lane >> 1) == g) asm volatile("red.relaxed.gpu.global.add.u32 [%0],%1;" ::"l"(fb + ((s >> 1) & 3)), "r"(FL_DATA) : "memory");
            __syncwarp();
        }
        bar_arrive(BAR_W, (NW + 1) * 32);
    }
}

__device__ __forceinline__ void stage2(const Params& p, unsigned char* sm, int g, int ig) {
    const int warp = warp_id(), lane = lane_id();
    constexpr uint32_t sb = SB;
    constexpr int NCW = 16, STEPS = NO / 4, TAB = NCW * ASEG, MB = TAB + SI * 8;
    static_assert(MB + 8 * NCW + 8 <= SM_AUX && MB % 8 == 0, "stage2 smem");
    if (threadIdx.x <= NCW) asm volatile("mbarrier.init.shared::cta.b64 [%0],1;" ::"r"(sb + MB + threadIdx.x * 8) : "memory");
    asm volatile("fence.proxy.async.shared::cta;" ::: "memory");
    __syncthreads();
    if (warp == 30) {
        const int e0 = (g * IG + ig) * SI, bytes = max(0, min((int)SI, p.E - e0)) * 8;
        if (elect_one()) {
            asm volatile("mbarrier.arrive.expect_tx.shared::cta.b64 _,[%0],%1;" ::"r"(sb + MB + NCW * 8), "r"(bytes) : "memory");
            for (int o = 0; o < bytes; o += 16384)
                asm volatile("cp.async.bulk.shared::cluster.global.mbarrier::complete_tx::bytes [%0],[%1],%2,[%3];" ::"r"(sb + TAB + o), "l"((const char*)(p.m + e0) + o), "r"(min(16384, bytes - o)), "r"(sb + MB + NCW * 8) : "memory");
        }
        __syncwarp();
    }
    if (warp == 31) poller<NCW, FL_GO2>(sm, g, ig >> 1, 0, p.units, p.units - 3 * N1, [&] {
            const int e0 = (g * IG + ig) * SI, n = min((int)SI, p.E - e0);
            if (n > 0 && elect_one()) asm volatile("cp.async.bulk.prefetch.L2.global [%0],%1;" ::"l"(p.m + e0), "r"(n * 8) : "memory");
            __syncwarp();
        });
    if (warp >= NCW) return;
    uint32_t* const fb = flag_base(sm, g, FL_GO3);
    const uint32_t f2 = (uint32_t)p.freq[0] * 0x10001u;
    const uint32_t vlane = slot_v(0) + (lane >> 4) * 8192 + ((lane >> 3) & 1) * VSEG + ig * 128 + (lane & 7) * 16;
    const uint32_t aoff = (ig >> 1) * 8192 + (ig & 1) * ASEG, buf = sb + warp * ASEG, mb = sb + MB + warp * 8;
    auto fetch = [&](uint32_t e) {
        if (elect_one()) {
            asm volatile("mbarrier.arrive.expect_tx.shared::cta.b64 _,[%0],%1;" ::"r"(mb), "n"(ASEG) : "memory");
            asm volatile("cp.async.bulk.shared::cluster.global.mbarrier::complete_tx::bytes [%0],[%1],%2,[%3];" ::"r"(buf),
                         "l"(g_ring + (slot_a((e >> 16) & 0xff) + aoff + ((e >> 2) & 0x1000))), "n"(ASEG), "r"(mb) : "memory");
        }
        __syncwarp();
    };
    mbar_wait(sb + MB + NCW * 8, 0);
    uint2 qn = make_uint2(0, 0);
    bool have = false;
    uint32_t ph = 0;
    for (int t = warp; t < p.units; t += NCW) {
        if (!have) { next_unit<true>(sb + SM_AUX, warp, t, NCW, qn); fetch(qn.x); }
        const uint2 qe = qn;
        mbar_wait(mb, ph); ph ^= 1;
        uint2 a[STEPS];
#pragma unroll
        for (int j = 0; j < STEPS; j++) asm volatile("ld.shared.v2.u32 {%0,%1},[%2];" : "=r"(a[j].x), "=r"(a[j].y) : "r"(buf + j * 256 + lane * 8) : "memory");
        have = next_unit<false>(sb + SM_AUX, warp, t + NCW, NCW, qn);
        uint32_t big = 0, x2[STEPS];
#pragma unroll
        for (int j = 0; j < STEPS; j++) {
            x2[j] = hmul2(__byte_perm(a[j].x, a[j].y, 0x7632), f2);
            a[j].x = __byte_perm(a[j].x, a[j].y, 0x5410);
            big |= (x2[j] & 0x7fff7fffu) + 0x3e003e00u;
        }
        const bool slow = __any_sync(0xffffffffu, big & 0x80008000u);
        if (have) fetch(qn.x + ((uint32_t)slow & p.zero));
        if (slow) {
#pragma unroll
            for (int j = 0; j < STEPS; j++) x2[j] = pack2(cos_slow(bf_lo(x2[j])), cos_slow(bf_hi(x2[j])));
        }
        const uint32_t tag = qe.x >> 31, cq = (qe.x >> (lane >> 4)) << 12;
        const uint32_t vo = ((qe.x >> 24) & 0x7f) * (PV * 8192) + vlane;
        uint2 m0[STEPS], m1[STEPS];
#pragma unroll
        for (int jj = 0; jj < STEPS + 1; jj++) {
            if (jj < STEPS) {
                asm volatile("ld.shared.v2.u32 {%0,%1},[%2];" : "=r"(m0[jj].x), "=r"(m0[jj].y) : "r"(sb + TAB + (a[jj].x & 0xffff) * 8) : "memory");
                asm volatile("ld.shared.v2.u32 {%0,%1},[%2];" : "=r"(m1[jj].x), "=r"(m1[jj].y) : "r"(sb + TAB + (a[jj].x >> 16) * 8) : "memory");
            }
            if (jj >= 1) {
                const int j = jj - 1;
                const uint32_t cf = pack2(__cosf(bf_lo(x2[j])), __cosf(bf_hi(x2[j]))), c2 = slow ? x2[j] : cf;
                const uint32_t d0 = __byte_perm(c2, 0, 0x1010), d1 = __byte_perm(c2, 0, 0x3232);
                st128(g_ring + (vo | ((cq >> (2 * j)) & 0x1000)) + j * 16384,
                      make_uint4((hmul2(m0[j].x, d0) & ~1u) | tag, hmul2(m0[j].y, d0), hmul2(m1[j].x, d1), hmul2(m1[j].y, d1)));
                if (p.zero) __nanosleep(0);
            }
        }
        __syncwarp();
        if (qe.y & 0x4000) asm volatile("fence.acq_rel.gpu;" ::: "memory");
        if (lane == 0) asm volatile("red.relaxed.gpu.global.add.u32 [%0],1;" ::"l"(fb + (qe.y & 63) * 4 + ((qe.y >> 6) & 3)) : "memory");
    }
}

__device__ __forceinline__ uint2 lock64(uint32_t a) {
    uint2 r;
    asm volatile("{.reg .b64 y; atom.shared.exch.b64 y,[%2],0xffffffffffffffff; mov.b64 {%0,%1},y;}" : "=r"(r.x), "=r"(r.y) : "r"(a) : "memory");
    return r;
}

__device__ __forceinline__ void stage3(const Params& p, unsigned char* sm, int g, int o) {
    const int warp = warp_id(), lane = lane_id();
    constexpr uint32_t sb = SB;
    if (threadIdx.x < 64) ((uint32_t*)(sm + SM_AUX + AUX_DUMMY))[threadIdx.x] = ~0u;
    for (int i = (g * NO + o) * 1024 + threadIdx.x; i < NO * (int)SO / 2; i += N3 * 1024) ((uint4*)g_agg)[i] = make_uint4(0, 0, 0, 0);
    __syncthreads();
    if (threadIdx.x == 0) asm volatile("red.release.gpu.global.add.u32 [%0],1;" ::"l"(&g_sync[SY_ZERO]) : "memory");
    const int t0 = p.pairs * 2 * STEP + (g * NO + o) * 1024 + threadIdx.x;
    static_assert(2 * STEP <= N3 * 1024, "remainder");
    if (t0 - lane < p.T) {
        const int t = min(t0, p.T - 1);
        const uint2 v = __ldg(p.m + p.idx_in[t]);
        wait_zeroed();
        if (t0 < p.T) red_agg(p.idx_out[t], v, dup_bf16(cos_any(rbf16(bf_lo(p.freq[0]) * bf_lo(p.angle[t])))));
        __syncwarp();
    }
    constexpr int NCW = 20, STEPS = IG / 4;
    uint32_t* const fb = flag_base(sm, g, FL_GO2);
    if (warp == 31) {
        poller<NCW, FL_GO3>(sm, g, (XO + o * XSEG) >> 12, (XO + XG) >> 12, p.units, p.units - 2 * N1, [&] {
            constexpr int H = (SO / 2 + 7) & ~7;
            const int e0 = (o * SO + g * H) & ~7, n = min(H + 8, p.E - e0) & ~7;
            if (n > 0 && elect_one()) {
                asm volatile("cp.async.bulk.prefetch.L2.global [%0],%1;" ::"l"(g_agg + e0), "r"(n * 8) : "memory");
                asm volatile("cp.async.bulk.prefetch.L2.global [%0],%1;" ::"l"(p.dist + e0), "r"(n * 2) : "memory");
            }
            __syncwarp();
        });
        wait_zeroed();
    } else if (warp < NCW) {
        const uint32_t dummy = sb + SM_AUX + AUX_DUMMY + lane * 8, r0 = (lane & 7) * 2;
        const uint32_t vlane = slot_v(0) + ring_off(0, o * VSEG) + lane * 16, xlane = ring_off(0, XO + o * XSEG) + lane * 4;
        const uint32_t clane = ring_off(0, XO + XG + o * IG) + (lane >> 3) * 4;
        for (int t = warp; t < p.units; t += NCW) {
            uint2 qe;
            next_unit<true>(sb + SM_AUX, warp, t, NCW, qe);
            const uint32_t tag = qe.x >> 31, ab = slot_a((qe.x >> 16) & 0xff);
            const uint4* vp = (const uint4*)(g_ring + (((qe.x >> 24) & 0x7f) * (PV * 8192) + vlane + (((qe.x >> (o >> 1)) & 1) << 12)));
            const uint32_t* xp = (const uint32_t*)(g_ring + (ab + xlane + ((qe.x >> 2) & 0x1000)));
            const uint32_t* cp = (const uint32_t*)(g_ring + (ab + clane + ((qe.x >> 3) & 0x1000)));
            uint4 v[STEPS]; uint32_t x[STEPS];
            const uint32_t cn = __ldcg(cp);
#pragma unroll
            for (int j = 0; j < STEPS; j++) x[j] = __ldcg(xp + j * 32);
#pragma unroll
            for (int j = 0; j < STEPS; j++) v[j] = ld128(vp + j * 32);
            for (int spins = 0;; spins++) {
                uint32_t bad = 0;
#pragma unroll
                for (int j = 0; j < STEPS; j++) bad |= v[j].x ^ tag;
                if (!__any_sync(0xffffffffu, bad & 1)) break;
                if (spins > (1 << 22)) __trap();
#pragma unroll
                for (int j = 0; j < STEPS; j++) v[j] = ld128(vp + j * 32);
            }
            uint32_t ad[2 * STEPS], dep = cn;
#pragma unroll
            for (int j = 0; j < STEPS; j++) {
                const uint32_t c = (cn >> (8 * j)) & 0xff;
                ad[2 * j] = r0 < c ? sb + (x[j] & 0xffff) * 8 : dummy;
                ad[2 * j + 1] = r0 + 1 < c ? sb + (x[j] >> 16) * 8 : dummy;
                dep ^= x[j];
            }
            if (lane == 0) asm volatile("red.relaxed.gpu.global.add.u32 [%0],%1;" ::"l"(fb + (qe.y & 63) * 4 + (((qe.y >> 6) + DV) & 3)), "r"(1 + (dep & p.zero)) : "memory");
            uint32_t pend = 0;
#pragma unroll
            for (int j0 = 0; j0 < 2 * STEPS; j0 += 4) {
                uint2 t[4];
#pragma unroll
                for (int j = 0; j < 4; j++) t[j] = lock64(ad[j0 + j]);
#pragma unroll
                for (int j = 0; j < 4; j++) {
                    const int jj = j0 + j;
                    const uint32_t vx = (jj & 1) ? v[jj / 2].z : v[jj / 2].x, vy = (jj & 1) ? v[jj / 2].w : v[jj / 2].y;
                    asm volatile("{.reg .pred p,q; setp.ne.u32 p,%4,0xffffffff; @p st.shared.v2.u32 [%1],{%2,%3}; setp.ne.and.u32 q,%1,%5,!p; @q or.b32 %0,%0,%6;}"
                                 : "+r"(pend) : "r"(ad[jj]), "r"(hadd2(t[j].x, vx)), "r"(hadd2(t[j].y, vy)), "r"(t[j].x), "r"(dummy), "r"(1u << jj) : "memory");
                }
            }
            while (__any_sync(0xffffffffu, pend)) {
                uint32_t a = dummy, vx = 0, vy = 0;
#pragma unroll
                for (int jj = 2 * STEPS - 1; jj >= 0; jj--)
                    if (pend & (1u << jj)) { a = ad[jj]; vx = (jj & 1) ? v[jj / 2].z : v[jj / 2].x; vy = (jj & 1) ? v[jj / 2].w : v[jj / 2].y; }
                const uint2 t = lock64(a);
                asm volatile("{.reg .pred p; setp.ne.u32 p,%4,0xffffffff; @p st.shared.v2.u32 [%1],{%2,%3}; @p and.b32 %0,%0,%5;}"
                             : "+r"(pend) : "r"(a), "r"(hadd2(t.x, vx)), "r"(hadd2(t.y, vy)), "r"(t.x), "r"(pend - 1) : "memory");
            }
        }
    }
    asm volatile("fence.proxy.async.shared::cta;" ::: "memory");
    __syncthreads();
    constexpr int CH = 8192;
    if (lane == 0 && warp * CH < (int)SO * 8) {
        asm volatile("fence.proxy.async.global;" ::: "memory");
        const int bytes = min(CH, (int)SO * 8 - warp * CH);
        if (g) asm volatile("cp.async.bulk.global.shared::cta.bulk_group [%0],[%1],%2;" ::"l"((char*)(g_rep + o * SO) + warp * CH), "r"(sb + warp * CH), "r"(bytes) : "memory");
        else asm volatile("cp.reduce.async.bulk.global.shared::cta.bulk_group.add.noftz.bf16 [%0],[%1],%2;" ::"l"((char*)(g_agg + o * SO) + warp * CH), "r"(sb + warp * CH), "r"(bytes) : "memory");
        asm volatile("cp.async.bulk.commit_group;" ::: "memory");
    }
}

__device__ __forceinline__ void mma_edge(float (&c)[4], uint32_t p01, uint32_t q01, uint32_t p23, uint32_t q23, uint2 b) {
    asm("mma.sync.aligned.m16n8k16.row.col.f32.bf16.bf16.f32 {%0,%1,%2,%3},{%4,%5,%6,%7},{%8,%9},{%0,%1,%2,%3};"
        : "+f"(c[0]), "+f"(c[1]), "+f"(c[2]), "+f"(c[3]) : "r"(p01), "r"(q01), "r"(p23), "r"(q23), "r"(b.x), "r"(b.y));
}
__device__ __forceinline__ uint2 b_frag(const uint16_t* w, int j0) {
    int lane; asm("mov.u32 %0,%%laneid;" : "=r"(lane));
    const int j = j0 + ((lane >> 2) & 1);
    const uint2 v = make_uint2(w[j] | ((uint32_t)w[4 + j] << 16), w[8 + j] | ((uint32_t)w[12 + j] << 16));
    return (lane & 3) == (lane >> 3) ? v : make_uint2(0, 0);
}
__device__ __forceinline__ void edge_gates(const uint16_t* w, uint32_t d2, uint4& sp, uint4& gp) {
    uint32_t rb[2][4];
#pragma unroll
    for (int k = 0; k < 2; k++)
#pragma unroll
        for (int r = 0; r < 4; r++) {
            uint32_t x; asm("sub.rn.bf16x2 %0,%1,%2;" : "=r"(x) : "r"(__byte_perm(d2, 0, k ? 0x3232 : 0x1010)), "r"(((const uint32_t*)w)[48 + r]));
            const uint32_t t = hmul2(hmul2(x, x), 0xc120c120u);
            rb[k][r] = pack2(__expf(bf_lo(t)), __expf(bf_hi(t)));
        }
    uint32_t o[4][2];
#pragma unroll
    for (int n = 0; n < 4; n++) {
        float c[4] = {};
        mma_edge(c, rb[0][0], rb[1][0], rb[0][1], rb[1][1], b_frag(w + (n >> 1) * 32, (n & 1) * 2));
        mma_edge(c, rb[0][2], rb[1][2], rb[0][3], rb[1][3], b_frag(w + (n >> 1) * 32 + 16, (n & 1) * 2));
        o[n][0] = pack2(c[0], c[1]); o[n][1] = pack2(c[2], c[3]);
    }
    gp = make_uint4(o[0][0], o[1][0], o[0][1], o[1][1]);
    sp = make_uint4(o[2][0], o[3][0], o[2][1], o[3][1]);
}
__device__ __forceinline__ uint4 edge_finish(const uint16_t* w, uint4 a, uint4 a2, uint4 sp, uint4 gp, uint4 mv) {
    float t0[4] = {}, t1[4] = {}, u0[4] = {}, u1[4] = {};
    mma_edge(t0, a.x, a.z, a.y, a.w, b_frag(w + 64, 0));
    mma_edge(t1, a.x, a.z, a.y, a.w, b_frag(w + 64, 2));
    mma_edge(t0, a2.x, a2.z, a2.y, a2.w, b_frag(w + 64, 0));
    mma_edge(t1, a2.x, a2.z, a2.y, a2.w, b_frag(w + 64, 2));
    const uint32_t p01 = pack2(t0[0] * bf_lo(sp.x), t0[1] * bf_hi(sp.x)), p23 = pack2(t1[0] * bf_lo(sp.y), t1[1] * bf_hi(sp.y));
    const uint32_t q01 = pack2(t0[2] * bf_lo(sp.z), t0[3] * bf_hi(sp.z)), q23 = pack2(t1[2] * bf_lo(sp.w), t1[3] * bf_hi(sp.w));
    mma_edge(u0, p01, q01, p23, q23, b_frag(w + 80, 0));
    mma_edge(u1, p01, q01, p23, q23, b_frag(w + 80, 2));
    return make_uint4(hadd2(mv.x, hmul2(pack2(u0[0], u0[1]), gp.x)), hadd2(mv.y, hmul2(pack2(u1[0], u1[1]), gp.y)),
                      hadd2(mv.z, hmul2(pack2(u0[2], u0[3]), gp.z)), hadd2(mv.w, hmul2(pack2(u1[2], u1[3]), gp.w)));
}

__device__ __forceinline__ void finish(const Params& p, unsigned char* sm) {
    __syncwarp();
    const int b = blockIdx.x, tid = threadIdx.x;
    const int role = ((const volatile uint32_t*)(sm + SM_AUX + AUX_MISC))[2];
    const uint16_t* w = (const uint16_t*)(sm + SM_AUX + AUX_W);
    if (role != 3) {
        __syncthreads();
        if (tid == 0) asm volatile("red.release.gpu.global.add.u32 [%0],1;" ::"l"(&g_sync[SY_END]) : "memory");
    }
    constexpr int EP = 3, es = NCTA * 1024;
    static_assert(EP * es * 2 >= E_CAP, "epilogue");
    uint4 sg[2 * EP];
    const int e0 = b * 1024 + tid, np = p.E / 2;
#pragma unroll
    for (int k = 0; k < EP; k++) sg[2 * k].x = __ldg((const uint32_t*)p.dist + min(e0 + k * es, np - 1));
#pragma unroll
    for (int k = 0; k < EP; k++) edge_gates(w, sg[2 * k].x, sg[2 * k], sg[2 * k + 1]);
    uint4 mv[EP];
#pragma unroll
    for (int k = 0; k < EP; k++) mv[k] = __ldg((const uint4*)p.m + min(e0 + k * es, np - 1));
    if (role == 3) {
        asm volatile("cp.async.bulk.wait_group 0;" ::: "memory");
        __syncthreads();
        if (tid == 0) asm volatile("red.release.gpu.global.add.u32 [%0],1;" ::"l"(&g_sync[SY_END]) : "memory");
    }
    uint4* const stash = (uint4*)sm + tid;
#pragma unroll
    for (int k = 0; k < EP; k++) { stash[(3 * k) * 1024] = sg[2 * k]; stash[(3 * k + 1) * 1024] = sg[2 * k + 1]; stash[(3 * k + 2) * 1024] = mv[k]; }
    if (tid == 0) {
        wait_flag(&g_sync[SY_END], NCTA);
        asm volatile("fence.acquire.gpu;" ::: "memory");
    }
    __syncthreads();
    uint4 av[EP], aw[EP];
#pragma unroll
    for (int k = 0; k < EP; k++) {
        const int e = min(e0 + k * es, np - 1);
        av[k] = __ldcg((const uint4*)g_agg + e); aw[k] = __ldcg((const uint4*)g_rep + e);
    }
#pragma unroll
    for (int k = 0; k < EP; k++) {
        const uint4 o = edge_finish(w, av[k], aw[k], stash[(3 * k) * 1024], stash[(3 * k + 1) * 1024], stash[(3 * k + 2) * 1024]);
        if (e0 + k * es < np) ((uint4*)p.out)[e0 + k * es] = o;
    }
    if (b == 0 && tid < 512) ((uint4*)(g_ring + slot_v(KV)))[tid] = make_uint4(0, 0, 0, 0);
    if (tid == 0) {
        g_info[b] = make_uint2(0, 0);
        if (atomicAdd(&g_sync[SY_EXIT], 1) == NCTA - 1)
            g_sync[SY_ZERO] = g_sync[SY_END] = g_sync[SY_EXIT] = g_sync[SY_WORK] = g_sync[SY_LOG] = g_sync[SY_LOG + 1] = 0;
    }
}

__global__ void __launch_bounds__(1024, 1) main_kernel(const __grid_constant__ Params p) {
    extern __shared__ __align__(128) unsigned char sm[];
    const int b = blockIdx.x, tid = threadIdx.x, warp = tid >> 5;
    if ((uint32_t)__cvta_generic_to_shared(sm) != SB) __trap();
    uint32_t* s_misc = (uint32_t*)(sm + SM_AUX + AUX_MISC);
    if (tid == 0) s_misc[0] = s_misc[4] = s_misc[5] = 0;
    __syncthreads();
    if ((tid & 31) == 0) {
        const int sl = b * 2 + (warp >> 4), j = warp & 15;
        if (warp == 31) s_misc[1] = upper_is_near(g_probe + (b & 127) * 32);
        else if (sl < NSL && j < (sl < KA ? PA : sl < KA + KV ? PV : 1) &&
                 upper_is_near(g_ring + (sl < KA ? slot_a(sl) : slot_v(sl - KA)) + j * 8192 + 4064))
            atomicOr(&s_misc[0], 1u << warp);
    }
    __syncwarp();
    __syncthreads();
    uint32_t me; asm("mov.u32 %0,%%smid;" : "=r"(me));
    me = 0x8000u | (s_misc[1] << 14) | (me & 0x3fff);
    if (tid == 0) {
        const u64 v = (u64)(s_misc[0] ^ (s_misc[1] ? ~0u : 0u)) | ((u64)me << 32);
        asm volatile("st.release.gpu.global.u64 [%0],%1;" ::"l"(&g_info[b]), "l"(v) : "memory");
    }
    for (int i = tid; i < (SM_AUX + AUX_CLS) / 16; i += 1024) ((uint4*)sm)[i] = make_uint4(0, 0, 0, 0);
    uint16_t* w = (uint16_t*)(sm + SM_AUX + AUX_W);
    if (tid < 160) {
        u64 v = 0; int spins = 0;
        while (tid < NCTA && !(v >> 32)) {
            asm volatile("ld.acquire.gpu.global.u64 %0,[%1];" : "=l"(v) : "l"(&g_info[tid]) : "memory");
            if (++spins > (1 << 22)) __trap();
        }
        __syncwarp();
        if (tid < NCTA) ((uint32_t*)(sm + SM_AUX + AUX_CLS))[tid] = (uint32_t)v;
        const uint32_t o = v >> 32;
        const uint32_t c = __reduce_add_sync(0xffffffffu, tid < NCTA ? 1u << (8 * ((o & 1) | ((o >> 13) & 2))) : 0u);
        const uint32_t r = __popc(__ballot_sync(0xffffffffu, tid < NCTA && ((o ^ me) & 0x4001) == 0 && (o > me || (o == me && tid > b))));
        if ((tid & 31) == 0) { atomicAdd(&s_misc[4], c); atomicAdd(&s_misc[5], r); }
    } else if (tid >= 256 && tid < 256 + 104) {
        const int j = tid - 256;
        w[j] = j < 32 ? p.w_rbf[j] : j < 64 ? p.w_sbf[j - 32] : j < 80 ? p.w_down[j - 64] : j < 96 ? p.w_up[j - 80] : p.centers[j - 96];
    }
    __syncthreads();
    int role, rank;
    {
        const uint32_t cnt = s_misc[4], cl = (me & 1) | ((me >> 13) & 2);
        rank = s_misc[5];
        const int c2 = (rank + 1) * IG / NO;
        if (__vminu4(cnt, NO * 0x01010101u) != NO * 0x01010101u) {
            role = b < N2 ? 2 : b < N2 + N3 ? 3 : 1;
            const int r = role == 2 ? b : b - N2;
            rank = role == 1 ? b - N2 - N3 : (r >> 1) | ((r & 1) << 8);
        } else if (rank < NO && (me & 1)) { role = 3; rank |= (cl >> 1) << 8; }
        else if (rank < NO && c2 != rank * IG / NO) { role = 2; rank = (c2 - 1) | ((cl >> 1) << 8); }
        else {
            role = 1;
            rank -= (me & 1) ? NO : min(c2, IG);
            for (uint32_t c = 0; c < cl; c++) rank += ((cnt >> (8 * c)) & 0xff) - ((c & 1) ? NO : IG);
        }
        if (tid == 0) s_misc[2] = role;
    }
    if (role == 1) stage1(p, sm, rank);
    else if (role == 2) stage2(p, sm, rank >> 8, rank & 255);
    else stage3(p, sm, rank >> 8, rank & 255);
    finish(p, sm);
}

__global__ void generic_scatter(const __grid_constant__ Params p) {
    const float f = bf_lo(p.freq[0]);
    for (int t = blockIdx.x * blockDim.x + threadIdx.x; t < p.T; t += gridDim.x * blockDim.x) {
        const uint2 v = __ldg(p.m + p.idx_in[t]);
        const uint32_t c2 = dup_bf16(cos_any(rbf16(f * bf_lo(p.angle[t]))));
        asm volatile("red.global.add.noftz.v2.bf16x2 [%0],{%1,%2};" ::"l"(p.out + p.idx_out[t]), "r"(hmul2(v.x, c2)), "r"(hmul2(v.y, c2)) : "memory");
    }
}
__global__ void __launch_bounds__(256) generic_finish(const __grid_constant__ Params p) {
    __shared__ __align__(16) uint16_t w[104];
    const int j = threadIdx.x, e = blockIdx.x * blockDim.x + j, ec = min(e, p.E - 1);
    if (j < 104) w[j] = j < 32 ? p.w_rbf[j] : j < 64 ? p.w_sbf[j - 32] : j < 80 ? p.w_down[j - 64] : j < 96 ? p.w_up[j - 80] : p.centers[j - 96];
    const uint2 a = p.out[ec], mv = p.m[ec];
    __syncthreads();
    uint4 s0, s1;
    edge_gates(w, p.dist[ec] * 0x10001u, s0, s1);
    const uint4 o = edge_finish(w, make_uint4(a.x, a.y, a.x, a.y), make_uint4(0, 0, 0, 0), s0, s1, make_uint4(mv.x, mv.y, mv.x, mv.y));
    if (e < p.E) p.out[e] = make_uint2(o.x, o.y);
}

extern "C" void kernel_launch(void* const* d_in, const int* in_sizes, int n_in, void* d_out, int out_size) {
    static int nsm = 0;
    if (!nsm) {
        cudaDeviceGetAttribute(&nsm, cudaDevAttrMultiProcessorCount, 0);
        cudaFuncSetAttribute(main_kernel, cudaFuncAttributeMaxDynamicSharedMemorySize, SMEM_BYTES);
    }
    Params p;
    p.m = (const uint2*)d_in[0]; p.idx_in = (const int*)d_in[1]; p.idx_out = (const int*)d_in[2];
    p.angle = (const uint16_t*)d_in[4]; p.freq = (const uint16_t*)d_in[6];
    p.dist = (const uint16_t*)d_in[3]; p.centers = (const uint16_t*)d_in[5]; p.w_rbf = (const uint16_t*)d_in[7];
    p.w_sbf = (const uint16_t*)d_in[8]; p.w_down = (const uint16_t*)d_in[9]; p.w_up = (const uint16_t*)d_in[10];
    p.out = (uint2*)d_out;
    p.E = in_sizes[3]; p.T = in_sizes[1];
    p.zero = 0;
    p.pairs = p.T / (2 * STEP); p.units = p.pairs + (NR / 2 + 1) * N1;
    bool fast = nsm >= NCTA && p.E <= E_CAP && p.E >= 8 && p.E % 2 == 0 && p.pairs >= 2 * N1 && p.units < 0xff00;
    static cudaTextureObject_t tex[3];
    static const void* tex_ptr[3];
    static int tex_n[3];
    for (int k = 0; k < 3 && fast; k++) {
        void* ptr = d_in[k == 2 ? 4 : 1 + k];
        if (tex_ptr[k] == ptr && tex_n[k] == p.T) continue;
        cudaResourceDesc rd = {};
        rd.resType = cudaResourceTypeLinear;
        rd.res.linear.devPtr = ptr;
        rd.res.linear.desc = k == 2 ? cudaCreateChannelDesc<uint2>() : cudaCreateChannelDesc<uint4>();
        rd.res.linear.sizeInBytes = (size_t)(p.T / 4) * (k == 2 ? 8 : 16);
        cudaTextureDesc td = {};
        td.readMode = cudaReadModeElementType;
        if (cudaCreateTextureObject(&tex[k], &rd, &td, nullptr) == cudaSuccess) { tex_ptr[k] = ptr; tex_n[k] = p.T; }
        else { cudaGetLastError(); tex_ptr[k] = nullptr; fast = false; }
    }
    p.tin = tex[0]; p.tout = tex[1]; p.tang = tex[2];
    if (!fast) {
        cudaMemsetAsync(d_out, 0, (size_t)p.E * 8);
        generic_scatter<<<nsm * 8, 256>>>(p);
        generic_finish<<<(p.E + 255) / 256, 256>>>(p);
        return;
    }
    void* args[] = {&p};
    cudaLaunchCooperativeKernel((const void*)main_kernel, dim3(NCTA), dim3(1024), args, SMEM_BYTES, cudaStreamPerThread);
}
```

```cpp
#include <cuda_runtime.h>
#include <cuda_bf16.h>
#include <stdint.h>

typedef unsigned long long u64;
constexpr uint32_t magic_of(uint32_t d) { return (uint32_t)(((1ull << 32) + d - 1) / d); }
constexpr uint32_t slice_of(uint32_t total, uint32_t n) {
    uint32_t d = ((total + n - 1) / n + 1) & ~1u;
    while (!((uint64_t)(n * d - 1) * magic_of(d) < ((uint64_t)n << 32))) d += 2;
    return d;
}
constexpr int E_CAP = 800000;
constexpr int NI = 32, NO = 28, NG = 2, IG = NI / NG;
constexpr uint32_t SI = slice_of(E_CAP, NI), SO = slice_of(E_CAP, NO);
constexpr uint32_t MI = magic_of(SI), MO = magic_of(SO);
constexpr int NCTA = 132, N2 = NI, N3 = NO * NG, N1 = NCTA - N2 - N3;
constexpr int C = 16, GB = NO * IG;
constexpr int NP = 5;
constexpr int NW = 28, STEP = NW * 256;
constexpr int NR = 4, LOGCAP = 8192, NCH = N1 * NW * NR * 8, KMAX = 4000;
static_assert(NR % 2 == 0 && NR >= 2 && NR <= 4 && NO % 4 == 0 && IG == 16, "shape");

constexpr int DA = 3, DS = 2, DV = 2, KA = DA * N1, KV = DV * N1, NSL = KA + KV + 1;
constexpr int ASEG = NO * C * 4, XSEG = IG * C * 2, VSEG = IG * C * 8;
constexpr int AG = IG * ASEG, XG = NO * XSEG, XO = IG / 2 * 4096, AXG = XO + XG + GB;
constexpr int PA = (AXG + 4095) / 4096, PV = NO * VSEG / 4096;
static_assert(2 * ASEG <= 4096 && AG == 2 * XG && (XO + XG) / 4096 == (AXG - 1) / 4096 && PA <= 15 && PV <= 14, "layout");
static_assert(DS >= DA - DV && DS <= DA && KA <= 256 && KV <= 128 && NSL <= 2 * NCTA && N1 <= 64, "ring");

constexpr uint32_t SB = 1024;
constexpr int SM_CNT = 0, SM_CB = NG * GB * 4, SM_LC = SM_CB + 2 * GB, SM_X = SM_LC + 256, SM_A = SM_X + NP * XG,
              SM_S1_END = SM_A + NP * AG;
constexpr int SM_AUX = SO * 8 + 512, QN = 256;
constexpr int AUX_Q = 0, AUX_PROG = QN * 8, AUX_CLS = AUX_PROG + 128, AUX_MISC = AUX_CLS + 576, AUX_DUMMY = AUX_MISC + 32,
              AUX_W = AUX_DUMMY + 256, AUX_END = AUX_W + 208;
constexpr int SMEM_BYTES = SM_AUX + AUX_END;
static_assert(SM_S1_END + 256 <= SM_AUX && SMEM_BYTES <= 232448 && SM_X % 128 == 0 && AUX_W % 16 == 0, "smem");

__device__ __align__(8192) unsigned char g_ring[(size_t)(KA * PA + KV * PV + 1) * 8192];
__device__ __align__(8192) unsigned char g_probe[8192];
__device__ uint2 g_log[N1 * NW * LOGCAP];
__device__ uint32_t g_chunks[NCH];
__device__ __align__(128) uint2 g_agg[NO * SO];
__device__ uint2 g_info[NCTA];
__device__ __align__(128) uint32_t g_sync[160];
constexpr int SY_ZERO = 0, SY_END = 32, SY_EXIT = 64, SY_WORK = 96, SY_LOG = 128;
constexpr int FL_GO2 = 0, FL_GO3 = 1;
constexpr uint32_t FL_DATA = 0x10000;

__device__ __forceinline__ int lane_id() { int v; asm volatile("mov.u32 %0,%%laneid;" : "=r"(v)); return v; }
__device__ __forceinline__ int warp_id() { int v; asm volatile("mov.u32 %0,%%tid.x;" : "=r"(v)); return __shfl_sync(0xffffffffu, v >> 5, 0); }
__device__ __forceinline__ float bf_lo(uint32_t v) { return __uint_as_float(v << 16); }
__device__ __forceinline__ float bf_hi(uint32_t v) { return __uint_as_float(v & 0xffff0000u); }
__device__ __forceinline__ float rbf16(float x) { return __bfloat162float(__float2bfloat16_rn(x)); }
__device__ __forceinline__ uint32_t hmul2(uint32_t a, uint32_t b) {
    uint32_t d; asm("mul.rn.bf16x2 %0,%1,%2;" : "=r"(d) : "r"(a), "r"(b)); return d;
}
__device__ __forceinline__ uint32_t hadd2(uint32_t a, uint32_t b) {
    uint32_t d; asm("add.rn.bf16x2 %0,%1,%2;" : "=r"(d) : "r"(a), "r"(b)); return d;
}
__device__ __forceinline__ uint32_t dup_bf16(float x) {
    uint32_t d; asm("cvt.rn.bf16x2.f32 %0,%1,%1;" : "=r"(d) : "f"(x)); return d;
}
__device__ __forceinline__ uint32_t pack2(float lo, float hi) {
    uint32_t d; asm("cvt.rn.bf16x2.f32 %0,%2,%1;" : "=r"(d) : "f"(lo), "f"(hi)); return d;
}
__device__ __noinline__ float cos_slow(float x) { return cosf(x); }
__device__ __forceinline__ float cos_any(float x) { return fabsf(x) < 32.f ? __cosf(x) : cos_slow(x); }
__device__ __forceinline__ void bar_sync(int id, int n) { asm volatile("barrier.sync.aligned %0,%1;" ::"r"(id), "r"(n) : "memory"); }
__device__ __forceinline__ void bar_arrive(int id, int n) { asm volatile("barrier.arrive.aligned %0,%1;" ::"r"(id), "r"(n) : "memory"); }
__device__ __forceinline__ uint32_t ld_relaxed(const uint32_t* p) {
    uint32_t v; asm volatile("ld.relaxed.gpu.global.u32 %0,[%1];" : "=r"(v) : "l"(p) : "memory"); return v;
}
__device__ __forceinline__ void st128(void* p, uint4 v) {
    asm volatile("{.reg .b64 a,b; .reg .b128 q; mov.b64 a,{%1,%2}; mov.b64 b,{%3,%4}; mov.b128 q,{a,b}; st.relaxed.gpu.global.b128 [%0],q;}" ::"l"(p), "r"(v.x), "r"(v.y), "r"(v.z), "r"(v.w) : "memory");
}
__device__ __forceinline__ uint4 ld128(const void* p) {
    uint4 v;
    asm volatile("{.reg .b64 a,b; .reg .b128 q; ld.relaxed.gpu.global.b128 q,[%4]; mov.b128 {a,b},q; mov.b64 {%0,%1},a; mov.b64 {%2,%3},b;}" : "=r"(v.x), "=r"(v.y), "=r"(v.z), "=r"(v.w) : "l"(p) : "memory");
    return v;
}
__device__ __forceinline__ void wait_flag(const uint32_t* p, uint32_t want) {
    int spins = 0;
    while ((ld_relaxed(p) & 0xffff) < want) {
        __nanosleep(50);
        if (++spins > (1 << 22)) __trap();
    }
}
__device__ __forceinline__ uint32_t slot_a(int s) { return s * (PA * 8192); }
__device__ __forceinline__ uint32_t slot_v(int s) { return KA * PA * 8192 + s * (PV * 8192); }
__device__ __forceinline__ uint32_t ring_off(uint32_t clsg, uint32_t off) {
    return ((off >> 12) << 13) + (((clsg >> (off >> 12)) & 1) << 12) + (off & 4095);
}
__device__ __forceinline__ uint32_t cls_of(const unsigned char* sm, int s, int g) {
    return ((const uint16_t*)(sm + SM_AUX + AUX_CLS))[s] ^ (g ? ~0u : 0u);
}
__device__ __forceinline__ uint32_t* flag_base(const unsigned char* sm, int g, int type) {
    return (uint32_t*)(g_ring + slot_v(KV) + ring_off(cls_of(sm, NSL - 1, g), type * 1024));
}
__device__ __forceinline__ uint32_t arrivals(int type, uint32_t k) {
    return type == FL_GO3 ? IG * ((k >> 2) + 1) : NO * ((k >> 2) + ((k & 3) >= DV));
}
__device__ __forceinline__ bool elect_one() {
    uint32_t r; asm volatile("{.reg .pred p; elect.sync _|p,0xffffffff; selp.u32 %0,1,0,p;}" : "=r"(r)); return r;
}
template <int NCW, int TYPE, class F>
__device__ __forceinline__ void poller(const unsigned char* sm, int g, int blk0, int blk1, int units, int hook_at, F hook) {
    const int lane = lane_id();
    constexpr uint32_t aux = SB + SM_AUX;
    constexpr int DR = TYPE == FL_GO2 ? DS : DA;
    const uint32_t lt = (1u << lane) - 1;
    const uint32_t* const fb = flag_base(sm, g, TYPE) + lane * 4;
    uint32_t ea[2][DR], ev[2][DV], k[2] = {0, 0}, want[2], v[2];
#pragma unroll
    for (int j = 0; j < 2; j++) {
        const int q = min(lane + j * 32, N1 - 1);
#pragma unroll
        for (int d = 0; d < DR; d++) {
            const uint32_t sa = q + d * N1, ca = cls_of(sm, sa, g);
            ea[j][d] = (((ca >> blk0) & 1) << 14) | (((ca >> blk1) & 1) << 15) | (sa << 16);
        }
#pragma unroll
        for (int d = 0; d < DV; d++) ev[j][d] = (cls_of(sm, KA + q + d * N1, g) & 0x3fff) | ((q + d * N1) << 24);
        want[j] = lane + j * 32 < N1 ? FL_DATA + arrivals(TYPE, 0) : ~0u;
        v[j] = 0;
    }
    int tail = 0, check = min(min(QN - N1, hook_at), units), spins = 0;
    while (true) {
        bool hit[2]; uint32_t bal[2];
#pragma unroll
        for (int j = 0; j < 2; j++) {
            hit[j] = v[j] >= want[j];
            bal[j] = __ballot_sync(0xffffffffu, hit[j]);
        }
        if (bal[0] | bal[1]) {
            asm volatile("fence.acquire.gpu;" ::: "memory");
            if (TYPE == FL_GO2) asm volatile("fence.proxy.async.global;" ::: "memory");
            asm volatile("fence.acq_rel.cta;" ::: "memory");
            spins = 0;
        } else if (++spins > (1 << 22)) __trap();
#pragma unroll
        for (int j = 0; j < 2; j++) {
            const uint32_t pos = tail + __popc(bal[j] & lt);
            const uint32_t hi = (lane + j * 32) | ((k[j] & 0xff) << 6) | (k[j] < DV ? 0x4000 : 0) | ((pos + 1) << 16);
            asm volatile("{.reg .pred p; .reg .b64 q; setp.ne.u32 p,%3,0; mov.b64 q,{%1,%2}; @p st.relaxed.cta.shared.u64 [%0],q;}"
                         ::"r"(aux + AUX_Q + (pos % QN) * 8), "r"(ea[j][0] | ev[j][0]), "r"(hi), "r"((uint32_t)hit[j]) : "memory");
            tail += __popc(bal[j]);
            k[j] += hit[j];
        }
#pragma unroll
        for (int j = 0; j < 2; j++) v[j] = ld_relaxed(fb + (j && lane + 32 < N1 ? 128 : 0) + (k[j] & 3));
#pragma unroll
        for (int j = 0; j < 2; j++) {
            const uint32_t a0 = ea[j][0], v0 = ev[j][0] ^ 0x80000000u;
#pragma unroll
            for (int d = 0; d < DR; d++) ea[j][d] = hit[j] ? (d + 1 < DR ? ea[j][(d + 1) % DR] : a0) : ea[j][d];
#pragma unroll
            for (int d = 0; d < DV; d++) ev[j][d] = hit[j] ? (d + 1 < DV ? ev[j][(d + 1) % DV] : v0) : ev[j][d];
            want[j] = hit[j] ? ((k[j] >> 2) + 1) * FL_DATA + arrivals(TYPE, k[j]) : want[j];
        }
        if (tail >= check) {
            if (tail >= units) break;
            if (tail >= hook_at) { hook(); hook_at = 0x7fffffff; }
            int limit;
            do {
                int prog; asm volatile("ld.volatile.shared.u32 %0,[%1];" : "=r"(prog) : "r"(aux + AUX_PROG + min(lane, NCW - 1) * 4) : "memory");
                limit = __reduce_min_sync(0xffffffffu, prog) + QN - N1;
            } while (tail > limit);
            check = min(min(limit, hook_at), units);
        }
    }
}
template <bool BLOCK>
__device__ __forceinline__ bool next_unit(uint32_t aux, int warp, int t, int step, uint2& e) {
    u64 v;
    while (true) {
        asm volatile("ld.acquire.cta.shared.u64 %0,[%1];" : "=l"(v) : "r"(aux + AUX_Q + (t % QN) * 8) : "memory");
        if (__all_sync(0xffffffffu, (int)(v >> 48) == t + 1)) break;
        if (!BLOCK) return false;
        __nanosleep(40);
    }
    if (((t + step) ^ t) & 64) asm volatile("st.volatile.shared.u32 [%0],%1;" ::"r"(aux + AUX_PROG + warp * 4), "r"(t + step) : "memory");
    e = make_uint2((uint32_t)v, (uint32_t)(v >> 32) & 0xffff);
    return true;
}
__device__ __forceinline__ int upper_is_near(unsigned char* q) {
    ((uint4*)q)[0] = ((uint4*)q)[1] = ((uint4*)(q + 4096))[0] = ((uint4*)(q + 4096))[1] = make_uint4(0, 0, 0, 0);
    uint32_t best[2] = {~0u, ~0u};
#pragma unroll
    for (int r = 0; r < 4; r++) {
        uint32_t t0, t1, v;
        asm volatile("mov.u32 %0,%%clock;" : "=r"(t0)::"memory");
        asm volatile("atom.global.exch.b32 %0,[%1],0;" : "=r"(v) : "l"(q + (r & 1) * 4096) : "memory");
        asm volatile("{.reg .pred p; setp.eq.u32 p,%1,0xffffffff; @p trap; mov.u32 %0,%%clock;}" : "=r"(t1) : "r"(v) : "memory");
        best[r & 1] = min(best[r & 1], t1 - t0);
    }
    return best[1] < best[0];
}

struct Params {
    const uint2* m; const int* idx_in; const int* idx_out; const uint16_t* angle; const uint16_t* freq;
    const uint16_t *dist, *centers, *w_rbf, *w_sbf, *w_down, *w_up; uint2* out;
    int E, T, pairs, units;
    uint32_t zero;
    cudaTextureObject_t tin, tout, tang;
};

__device__ __forceinline__ void red_agg(uint32_t out, uint2 v, uint32_t c2) {
    asm volatile("red.global.add.noftz.v2.bf16x2 [%0],{%1,%2};" ::"l"(g_agg + out), "r"(hmul2(v.x, c2)), "r"(hmul2(v.y, c2)) : "memory");
}
__device__ __forceinline__ void decode_entry(uint32_t e0, uint32_t e1, uint32_t& in, uint32_t& out) {
    const uint32_t bx = e1 >> 21, g = bx >= GB, rem = bx - g * GB;
    in = (g * IG + rem % IG) * SI + (e0 & 0xffff);
    out = rem / IG * SO + (e1 & 0xffff);
}
__device__ __forceinline__ void wait_zeroed() {
    wait_flag(&g_sync[SY_ZERO], N3);
    asm volatile("fence.acquire.gpu;" ::: "memory");
}
constexpr int BAR_ATOMS = 1, BAR_STS = 2, BAR_PUB = 4, BAR_PUBFREE = 6, BAR_W = 8;
constexpr int NT_STS = (NW + 2) * 32, NT_ATOMS = (NW + 1) * 32;
__device__ __forceinline__ void mbar_arrive(uint32_t bar) {
    __syncwarp();
    if (elect_one()) asm volatile("mbarrier.arrive.shared::cta.b64 _,[%0];" ::"r"(bar) : "memory");
}
__device__ __forceinline__ void mbar_wait(uint32_t bar, uint32_t parity) {
    asm volatile("{.reg .pred p; .reg .u32 n; mbarrier.try_wait.parity.shared::cta.b64 p,[%0],%1; @p bra D; mov.u32 n,0;\n"
                 "W: mbarrier.try_wait.parity.shared::cta.b64 p,[%0],%1,2000; @p bra D;\n"
                 "add.u32 n,n,1; setp.lt.u32 p,n,0x4000000; @p bra W; trap;\nD:}" ::"r"(bar), "r"(parity) : "memory");
}
__device__ __forceinline__ uint32_t mad(uint32_t a, uint32_t b, uint32_t c) {
    uint32_t d; asm("mad.lo.u32 %0,%1,%2,%3;" : "=r"(d) : "r"(a), "r"(b), "r"(c)); return d;
}
template <bool R, int G> struct Kind { static constexpr bool replay = R; static constexpr int group = G; };

__device__ __forceinline__ void stage1(const Params& p, unsigned char* sm, int pid) {
    const int warp = warp_id(), lane = lane_id();
    constexpr uint32_t sb = SB;
    uint4 ra[2], rb[2]; uint2 rc[2];
    volatile int* const s_next = (volatile int*)(sm + SM_LC + 64);
    const int total = p.pairs * 2;
    constexpr uint32_t mb = sb + SM_LC;
    if (threadIdx.x < 4) asm volatile("mbarrier.init.shared::cta.b64 [%0],1;" ::"r"(mb + threadIdx.x * 8) : "memory");
    if (threadIdx.x == 0) s_next[2] = 0x7ffffff0;
    if (threadIdx.x < 32) s_next[16 + threadIdx.x] = 2 * C;
    __syncthreads();
    if (warp < NW) {
        constexpr uint32_t cb = sb + SM_CNT, xdum = (uint32_t)(SM_LC + 128 - SM_CNT) << 19;
        constexpr uint32_t xk = sb + SM_X, ak = sb + SM_A - 2 * xk;
        uint32_t cur0 = xk + (lane & p.zero), nxt0 = cur0 + 2 * XG - C * 2, cur1 = cur0, nxt1 = nxt0;
        uint32_t fresh = cur0 + 4 * XG - C * 2, n0 = 0, wpos = 0, chunk = 0;
        int h_in = pid * 2, np = 0;
        uint2* const log = g_log + (pid * NW + warp) * LOGCAP;
        const uint32_t ltmask = ((1u << lane) - 1) | p.zero, tq = (warp * 64 + lane) | p.zero;
        auto load_in = [&](int h) {
            const int q = h_in * (STEP / 4) + tq + h * 32;
            asm volatile("tex.1d.v4.u32.s32 {%0,%1,%2,%3},[%4,{%5}];" : "=r"(ra[h].x), "=r"(ra[h].y), "=r"(ra[h].z), "=r"(ra[h].w) : "l"(p.tin), "r"(q));
            asm volatile("tex.1d.v4.u32.s32 {%0,%1,%2,%3},[%4,{%5}];" : "=r"(rb[h].x), "=r"(rb[h].y), "=r"(rb[h].z), "=r"(rb[h].w) : "l"(p.tout), "r"(q));
            asm volatile("{.reg .b32 z,w; tex.1d.v4.u32.s32 {%0,%1,z,w},[%2,{%3}];}" : "=r"(rc[h].x), "=r"(rc[h].y) : "l"(p.tang), "r"(q));
        };
        auto direct = [&](uint32_t first, uint32_t stride, uint32_t count, auto range, auto gate) {
            const float f = bf_lo(p.freq[0]);
            for (uint32_t c0 = first;; c0 += stride * 4) {
                uint2 e[4], v[4]; uint32_t ok = 0, big = 0;
#pragma unroll
                for (int k = 0; k < 4; k++) {
                    uint32_t lo = 0, hi = 0;
                    if (c0 + k * stride < count) range(c0 + k * stride, lo, hi);
                    e[k] = make_uint2(0, 0);
                    if (lo + lane < hi) { e[k] = __ldcg(g_log + lo + lane); ok |= 1u << k; }
                }
                __syncwarp();
                if (c0 == first) gate();
#pragma unroll
                for (int k = 0; k < 4; k++) {
                    uint32_t in;
                    decode_entry(e[k].x, e[k].y, in, e[k].y);
                    v[k] = __ldcg(p.m + in);
                    e[k].x = __float_as_uint(rbf16(f * bf_hi(e[k].x)));
                    big = max(big, e[k].x & 0x7fffffffu);
                }
                const bool slow = __any_sync(0xffffffffu, big >= 0x42000000u);
#pragma unroll
                for (int k = 0; k < 4; k++) {
                    float c = __cosf(__uint_as_float(e[k].x));
                    if (slow) c = cos_slow(__uint_as_float(e[k].x));
                    if ((ok >> k) & 1) red_agg(e[k].y, v[k], dup_bf16(c));
                }
                __syncwarp();
                if (c0 + stride * 4 >= count) break;
            }
        };
        auto drain = [&]() {
            const uint32_t lb = (pid * NW + warp) * LOGCAP;
            __syncwarp();
            direct(0, 1, (wpos - n0 + 31) / 32, [&](uint32_t c, uint32_t& lo, uint32_t& hi) { lo = lb + n0 + c * 32; hi = lb + wpos; },
                   [&] { wait_zeroed(); __syncwarp(); });
            wpos = n0;
        };
        auto load_log = [&](int j) {
            uint2 e[8];
#pragma unroll
            for (int k = 0; k < 8; k++) {
                const uint32_t ch = __shfl_sync(0xffffffffu, chunk, k * NR + j);
                e[k] = make_uint2(0, xdum + (lane << 21));
                if (j < NR && lane < (ch >> 24)) e[k] = __ldcg(g_log + (ch & 0xffffff) * 32 + lane);
            }
#pragma unroll
            for (int h = 0; h < 2; h++) {
                ra[h] = make_uint4(e[h * 4].x, e[h * 4].y, e[h * 4 + 1].x, e[h * 4 + 1].y);
                rb[h] = make_uint4(e[h * 4 + 2].x, e[h * 4 + 2].y, e[h * 4 + 3].x, e[h * 4 + 3].y);
            }
        };
        auto step = [&](const int k2, auto kind) {
            constexpr bool R = decltype(kind)::replay;
            constexpr int G = decltype(kind)::group;
            uint32_t pa[8], aw[8], xw[8], r[8];
#pragma unroll
            for (int h = 0; h < 2; h++) {
                if (!R) {
                    const uint32_t in[4] = {ra[h].x, ra[h].y, ra[h].z, ra[h].w}, out[4] = {rb[h].x, rb[h].y, rb[h].z, rb[h].w};
#pragma unroll
                    for (int k = 0; k < 4; k++) {
                        const uint32_t i = __umulhi(in[k], MI), o = __umulhi(out[k], MO);
                        aw[h * 4 + k] = __byte_perm(in[k] - i * SI, k < 2 ? rc[h].x : rc[h].y, (k & 1) ? 0x7610 : 0x5410);
                        pa[h * 4 + k] = mad(i, NO, o);
                        xw[h * 4 + k] = mad(i, 1u << 21, mad(o, (IG << 21) - SO, out[k]));
                        asm("{.reg .pred p; setp.ge.u32 p,%1,%2; @p add.u32 %0,%0,%3;}" : "+r"(xw[h * 4 + k]) : "r"(in[k]), "n"(IG * SI), "n"((GB - IG) << 21));
                    }
                } else {
#pragma unroll
                    for (int k = h * 4; k < h * 4 + 4; k++) {
                        const uint4 q4 = (k & 2) ? rb[h] : ra[h];
                        const uint2 e = (k & 1) ? make_uint2(q4.z, q4.w) : make_uint2(q4.x, q4.y);
                        aw[k] = e.x; xw[k] = e.y;
                        pa[k] = mad((e.y >> 21) % IG, NO, (e.y >> 25) + (e.y >= GB << 21 ? GB - NO : 0));
                    }
                }
                if (h == 0) {
                    mbar_wait(mb + G * 8, k2 & 1);
                    if (!R) {
                        if (G) asm volatile("ld.volatile.shared.u32 %0,[%1];" : "=r"(h_in) : "r"(mb + 64) : "memory");
                        else h_in++;
                    }
                }
#pragma unroll
                for (int k = h * 4; k < h * 4 + 4; k++)
                    asm volatile("atom.shared.add.u32 %0,[%1+%2],1;" : "=r"(r[k]) : "r"(xw[k] >> 19), "n"(cb) : "memory");
            }
            bar_arrive(BAR_ATOMS, NT_ATOMS);
            mbar_wait(mb + 16 + G * 8, k2 & 1);
            if (!R) {
                load_in(0);
                if (p.zero) __nanosleep(0);
            }
            uint32_t ovf = 0;
#pragma unroll
            for (int k = 0; k < 8; k++) {
                const bool lo = r[k] < C, hi = xw[k] >= GB << 21;
                const uint32_t s2 = r[k] * 2 + (hi ? (lo ? cur1 : nxt1) : (lo ? cur0 : nxt0));
                asm volatile("{.reg .pred p; .reg .b16 a,b; setp.lt.u32 p,%5,%6; mov.b32 {a,b},%4;"
                             " @p st.shared.u32 [%1+%8],%2; @p st.shared.u16 [%3],a; @!p or.b32 %0,%0,%7;}"
                             : "+r"(ovf) : "r"(mad(pa[k], C * 2, s2) * 2), "r"(aw[k]), "r"((xw[k] >> 16) + s2), "r"(xw[k]), "r"(r[k]),
                               "n"(2 * C), "r"(R && xw[k] >= xdum ? 0u : 1u << k), "n"(ak) : "memory");
            }
            bar_arrive(BAR_STS + G, NT_STS);
            if (!R) {
                if (p.zero) __nanosleep(0);
                load_in(1);
            }
            uint32_t bal = __ballot_sync(0xffffffffu, ovf != 0);
            while (bal) {
                uint32_t e0 = aw[7], e1 = xw[7];
#pragma unroll
                for (int k = 6; k >= 0; k--)
                    if (ovf & (1u << k)) { e0 = aw[k]; e1 = xw[k]; }
                asm volatile("{.reg .pred p; setp.ne.u32 p,%3,0; @p st.global.v2.u32 [%0],{%1,%2};}" ::"l"(log + (wpos + __popc(bal & ltmask))), "r"(e0), "r"(e1), "r"(ovf) : "memory");
                wpos += __popc(bal);
                ovf &= ovf - 1;
                bal = __ballot_sync(0xffffffffu, ovf != 0);
            }
            if (R) load_log((k2 - np) * 2 + G + 1);
            if (G) { cur1 = nxt1 + C * 2; nxt1 = fresh - XG; }
            else if (!R || k2 != np + NR / 2 - 1) { cur0 = nxt0 + C * 2; nxt0 = fresh; }
            fresh += fresh == xk + (NP - 1) * XG - C * 2 ? -(NP - 1) * XG : XG;
        };
        u64* const logsync = (u64*)&g_sync[SY_LOG];
        for (int stop = total - 2 * 2 * N1; h_in < total;) {
            load_in(0); load_in(1);
            do {
                step(np, Kind<false, 0>());
                step(np, Kind<false, 1>());
                np++;
            } while (h_in < stop && wpos <= LOGCAP - 512);
            if (wpos > LOGCAP - 512) drain();
            if (h_in >= stop && stop < total) {
                const uint32_t nch = min((wpos + 31) / 32, (LOGCAP - 256 * NR) / 32);
                uint32_t base = 0;
                if (lane == 0) base = (uint32_t)atomicAdd(logsync, (u64)nch);
                base = __shfl_sync(0xffffffffu, base, 0);
                const uint32_t mine = min(nch, NCH - min(base, NCH));
                for (uint32_t c = lane; c < mine; c += 32)
                    g_chunks[base + c] = ((pid * NW + warp) * (LOGCAP / 32) + c) | (min(wpos - c * 32, 32u) << 24);
                n0 = min(wpos, mine * 32);
                __syncwarp();
                if (elect_one()) {
                    asm volatile("red.release.gpu.global.add.u64 [%0],%1;" ::"l"(logsync), "l"(1ull << 32) : "memory");
                    if (n0 >= 2) asm volatile("cp.async.bulk.prefetch.L2.global [%0],%1;" ::"l"(log), "r"(n0 / 2 * 16) : "memory");
                }
                __syncwarp();
                stop = total;
            }
        }
        {
            u64 v; int spins = 0;
            do {
                asm volatile("ld.acquire.gpu.global.u64 %0,[%1];" : "=l"(v) : "l"(logsync) : "memory");
                if (++spins > (1 << 22)) __trap();
            } while ((v >> 32) < N1 * NW);
            const uint32_t idx = (((lane / NR) * NW + warp) * NR + lane % NR) * N1 + pid;
            if (lane < 8 * NR && idx < (uint32_t)v) chunk = __ldcg(g_chunks + idx);
            __syncwarp();
        }
        if (wpos > LOGCAP - 256 * NR) drain();
        load_log(0);
#pragma unroll 1
        for (int k2 = np; k2 < np + NR / 2; k2++) {
            step(k2, Kind<true, 0>());
            step(k2, Kind<true, 1>());
        }
        uint2* const rng = (uint2*)(sm + SM_S1_END);
        if (lane == 0) rng[warp] = make_uint2(n0, wpos);
        __syncwarp();
        for (int g = 0; g < NG; g++) {
            mbar_wait(mb + g * 8, (np + NR / 2) & 1);
            mbar_wait(mb + 16 + g * 8, (np + NR / 2) & 1);
            bar_arrive(BAR_ATOMS, NT_ATOMS);
            bar_arrive(BAR_STS + g, NT_STS);
        }
        const uint2 mine = lane < NW ? rng[lane] : make_uint2(0, 0);
        const uint32_t nch = (mine.y - mine.x + 31) / 32;
        uint32_t end = nch;
#pragma unroll
        for (int d = 1; d < 32; d *= 2) {
            const uint32_t t = __shfl_up_sync(0xffffffffu, end, d);
            if (lane >= d) end += t;
        }
        direct(warp, NW, __shfl_sync(0xffffffffu, end, 31), [&](uint32_t c, uint32_t& lo, uint32_t& hi) {
            const int w = __popc(__ballot_sync(0xffffffffu, end <= c));
            const uint32_t lb = (pid * NW + w) * LOGCAP;
            lo = lb + __shfl_sync(0xffffffffu, mine.x + (c - (end - nch)) * 32, w);
            hi = lb + __shfl_sync(0xffffffffu, mine.y, w);
        }, [&] { bar_sync(BAR_W, (NW + 1) * 32); });
    } else if (warp == NW) {
        const int row = min(lane, NO - 1), swz = (row >> 1) & 3;
        mbar_arrive(mb);
        int pn = N1 + pid, pnn = 0, nc = 0x7ffffff0;
        for (int s = 0; s < nc; s++) {
            const int hn = min(pn * 2 + (s & 1), total);
            if (hn == total) nc = min(nc, s + 2 + NR + 2);
            const uint32_t sub = s == nc - 4 ? 0 : C, bias = s == nc - 2 ? C : 0;
            uint4* cp = (uint4*)(sm + SM_CNT + (s & 1) * GB * 4) + row * 4;
            bar_sync(BAR_ATOMS, NT_ATOMS);
            uint4 c[4];
#pragma unroll
            for (int j = 0; j < 4; j++) c[j] = cp[j ^ swz];
            __syncwarp();
#pragma unroll
            for (int j = 0; j < 4; j++)
                cp[j ^ swz] = make_uint4(min(max(c[j].x, C), 2 * C) - sub, min(max(c[j].y, C), 2 * C) - sub,
                                         min(max(c[j].z, C), 2 * C) - sub, min(max(c[j].w, C), 2 * C) - sub);
            if (lane == 0 && !(s & 1)) { s_next[0] = hn; s_next[2] = nc; }
            mbar_arrive(mb + ((s + 1) & 1) * 8);
            uint4 w = make_uint4(0, 0, 0, 0);
#pragma unroll
            for (int j = 0; j < 4; j++) {
                const int sh = (j ^ swz) * 8;
                w.x |= min(c[j].x - bias, C) << sh; w.y |= min(c[j].y - bias, C) << sh;
                w.z |= min(c[j].z - bias, C) << sh; w.w |= min(c[j].w - bias, C) << sh;
            }
            mbar_wait(mb + 16 + (s & 1) * 8, (s >> 1) & 1);
            ((uint4*)(sm + SM_CB + (s & 1) * GB))[row] = w;
            asm volatile("fence.proxy.async.shared::cta;" ::: "memory");
            bar_arrive(BAR_STS + (s & 1), NT_STS);
            if (s & 1) pn = min(2 * N1 + __shfl_sync(0xffffffffu, pnn, 0), p.pairs);
            else if (hn < total && s / 2 + 2 < KMAX) {
                if (lane == 0) asm volatile("atom.relaxed.gpu.global.add.u32 %0,[%1],1;" : "=r"(pnn) : "l"(&g_sync[SY_WORK]) : "memory");
            } else pnn = p.pairs;
            const int hp = pn * 2 + ((s & 1) ^ 1);
            if (hp < total && elect_one())
                asm volatile("cp.async.bulk.prefetch.L2.global [%0],%1;" ::"l"(p.angle + hp * STEP), "r"(STEP * 2) : "memory");
            __syncwarp();
        }
    } else if (warp < NW + 3) {
        const int g = warp - NW - 1;
        mbar_arrive(mb + 16 + g * 8);
        const uint32_t* const fb = flag_base(sm, g, lane & 1) + pid * 4;
        for (int s = g; s < s_next[2]; s += 2) {
            const int k = s >> 1, slot = k % DA * N1 + pid, slots = k % DS * N1 + pid, pl = s % NP;
            const uint32_t cls = __shfl_sync(0xffffffffu, cls_of(sm, slot, g), 0), clss = __shfl_sync(0xffffffffu, cls_of(sm, slots, g), 0);
            if (k >= DS) {
                const uint32_t kw = k - ((lane & 1) ? DS : DA - DV);
                wait_flag(fb + (kw & 3), arrivals(lane & 1, kw));
                __syncwarp();
                asm volatile("fence.proxy.async.global;" ::: "memory");
            }
            bar_sync(BAR_STS + g, NT_STS);
            asm volatile("fence.proxy.async.shared::cta;" ::: "memory");
            if (elect_one()) {
                unsigned char* dst = g_ring + slot_a(slot);
#pragma unroll
                for (int j = 0; j < IG / 2; j++)
                    asm volatile("cp.async.bulk.global.shared::cta.bulk_group [%0],[%1],%2;" ::"l"(g_ring + slot_a(slots) + ring_off(clss, j * 4096)),
                                 "r"(sb + SM_A + pl * AG + j * 2 * ASEG), "n"(2 * ASEG) : "memory");
#pragma unroll
                for (int j = 0; j * 4096 < XG; j++)
                    asm volatile("cp.async.bulk.global.shared::cta.bulk_group [%0],[%1],%2;" ::"l"(dst + ring_off(cls, XO + j * 4096)),
                                 "r"(sb + SM_X + pl * XG + j * 4096), "r"(min(4096, XG - j * 4096)) : "memory");
                asm volatile("cp.async.bulk.global.shared::cta.bulk_group [%0],[%1],%2;" ::"l"(dst + ring_off(cls, XO + XG)),
                             "r"(sb + SM_CB + g * GB), "r"(GB) : "memory");
                asm volatile("cp.async.bulk.commit_group;" ::: "memory");
                asm volatile("cp.async.bulk.wait_group 0;" ::: "memory");
            }
            __syncwarp();
            mbar_arrive(mb + 16 + g * 8);
            bar_sync(BAR_PUBFREE + g, 64);
            bar_arrive(BAR_PUB + g, 64);
        }
    } else if (warp == NW + 3) {
        uint32_t* const fb = flag_base(sm, (lane >> 1) & 1, lane & 1) + pid * 4;
        bar_arrive(BAR_PUBFREE, 64);
        bar_arrive(BAR_PUBFREE + 1, 64);
        for (int s = 0; s < s_next[2]; s++) {
            if (s == 4) { wait_zeroed(); __syncwarp(); }
            const int g = s & 1;
            bar_sync(BAR_PUB + g, 64);
            if (s + 2 < s_next[2]) bar_arrive(BAR_PUBFREE + g, 64);
            asm volatile("fence.acq_rel.gpu;" ::: "memory");
            if ((lane >> 1) == g) asm volatile("red.relaxed.gpu.global.add.u32 [%0],%1;" ::"l"(fb + ((s >> 1) & 3)), "r"(FL_DATA) : "memory");
            __syncwarp();
        }
        bar_arrive(BAR_W, (NW + 1) * 32);
    }
}

__device__ __forceinline__ void stage2(const Params& p, unsigned char* sm, int g, int ig) {
    const int warp = warp_id(), lane = lane_id();
    constexpr uint32_t sb = SB;
    constexpr int NCW = 16, STEPS = NO / 4, TAB = NCW * ASEG, MB = TAB + SI * 8;
    static_assert(MB + 8 * NCW + 8 <= SM_AUX && MB % 8 == 0, "stage2 smem");
    if (threadIdx.x <= NCW) asm volatile("mbarrier.init.shared::cta.b64 [%0],1;" ::"r"(sb + MB + threadIdx.x * 8) : "memory");
    asm volatile("fence.proxy.async.shared::cta;" ::: "memory");
    __syncthreads();
    if (warp == 30) {
        const int e0 = (g * IG + ig) * SI, bytes = max(0, min((int)SI, p.E - e0)) * 8;
        if (elect_one()) {
            asm volatile("mbarrier.arrive.expect_tx.shared::cta.b64 _,[%0],%1;" ::"r"(sb + MB + NCW * 8), "r"(bytes) : "memory");
            for (int o = 0; o < bytes; o += 16384)
                asm volatile("cp.async.bulk.shared::cluster.global.mbarrier::complete_tx::bytes [%0],[%1],%2,[%3];" ::"r"(sb + TAB + o), "l"((const char*)(p.m + e0) + o), "r"(min(16384, bytes - o)), "r"(sb + MB + NCW * 8) : "memory");
        }
        __syncwarp();
    }
    if (warp == 31) poller<NCW, FL_GO2>(sm, g, ig >> 1, 0, p.units, p.units - 3 * N1, [&] {
            const int e0 = (g * IG + ig) * SI, n = min((int)SI, p.E - e0);
            if (n > 0 && elect_one()) asm volatile("cp.async.bulk.prefetch.L2.global [%0],%1;" ::"l"(p.m + e0), "r"(n * 8) : "memory");
            __syncwarp();
        });
    if (warp >= NCW) return;
    uint32_t* const fb = flag_base(sm, g, FL_GO3);
    const uint32_t f2 = (uint32_t)p.freq[0] * 0x10001u;
    const uint32_t vlane = slot_v(0) + (lane >> 4) * 8192 + ((lane >> 3) & 1) * VSEG + ig * 128 + (lane & 7) * 16;
    const uint32_t aoff = (ig >> 1) * 8192 + (ig & 1) * ASEG, buf = sb + warp * ASEG, mb = sb + MB + warp * 8;
    auto fetch = [&](uint32_t e) {
        if (elect_one()) {
            asm volatile("mbarrier.arrive.expect_tx.shared::cta.b64 _,[%0],%1;" ::"r"(mb), "n"(ASEG) : "memory");
            asm volatile("cp.async.bulk.shared::cluster.global.mbarrier::complete_tx::bytes [%0],[%1],%2,[%3];" ::"r"(buf),
                         "l"(g_ring + (slot_a((e >> 16) & 0xff) + aoff + ((e >> 2) & 0x1000))), "n"(ASEG), "r"(mb) : "memory");
        }
        __syncwarp();
    };
    mbar_wait(sb + MB + NCW * 8, 0);
    uint2 qn = make_uint2(0, 0);
    bool have = false;
    uint32_t ph = 0;
    for (int t = warp; t < p.units; t += NCW) {
        if (!have) { next_unit<true>(sb + SM_AUX, warp, t, NCW, qn); fetch(qn.x); }
        const uint2 qe = qn;
        mbar_wait(mb, ph); ph ^= 1;
        uint2 a[STEPS];
#pragma unroll
        for (int j = 0; j < STEPS; j++) asm volatile("ld.shared.v2.u32 {%0,%1},[%2];" : "=r"(a[j].x), "=r"(a[j].y) : "r"(buf + j * 256 + lane * 8) : "memory");
        have = next_unit<false>(sb + SM_AUX, warp, t + NCW, NCW, qn);
        uint32_t big = 0, x2[STEPS];
#pragma unroll
        for (int j = 0; j < STEPS; j++) {
            x2[j] = hmul2(__byte_perm(a[j].x, a[j].y, 0x7632), f2);
            a[j].x = __byte_perm(a[j].x, a[j].y, 0x5410);
            big |= (x2[j] & 0x7fff7fffu) + 0x3e003e00u;
        }
        const bool slow = __any_sync(0xffffffffu, big & 0x80008000u);
        if (have) fetch(qn.x + ((uint32_t)slow & p.zero));
        if (slow) {
#pragma unroll
            for (int j = 0; j < STEPS; j++) x2[j] = pack2(cos_slow(bf_lo(x2[j])), cos_slow(bf_hi(x2[j])));
        }
        const uint32_t tag = qe.x >> 31, cq = (qe.x >> (lane >> 4)) << 12;
        const uint32_t vo = ((qe.x >> 24) & 0x7f) * (PV * 8192) + vlane;
        uint2 m0[STEPS], m1[STEPS];
#pragma unroll
        for (int jj = 0; jj < STEPS + 1; jj++) {
            if (jj < STEPS) {
                asm volatile("ld.shared.v2.u32 {%0,%1},[%2];" : "=r"(m0[jj].x), "=r"(m0[jj].y) : "r"(sb + TAB + (a[jj].x & 0xffff) * 8) : "memory");
                asm volatile("ld.shared.v2.u32 {%0,%1},[%2];" : "=r"(m1[jj].x), "=r"(m1[jj].y) : "r"(sb + TAB + (a[jj].x >> 16) * 8) : "memory");
            }
            if (jj >= 1) {
                const int j = jj - 1;
                const uint32_t cf = pack2(__cosf(bf_lo(x2[j])), __cosf(bf_hi(x2[j]))), c2 = slow ? x2[j] : cf;
                const uint32_t d0 = __byte_perm(c2, 0, 0x1010), d1 = __byte_perm(c2, 0, 0x3232);
                st128(g_ring + (vo | ((cq >> (2 * j)) & 0x1000)) + j * 16384,
                      make_uint4((hmul2(m0[j].x, d0) & ~1u) | tag, hmul2(m0[j].y, d0), hmul2(m1[j].x, d1), hmul2(m1[j].y, d1)));
                if (p.zero) __nanosleep(0);
            }
        }
        __syncwarp();
        if (qe.y & 0x4000) asm volatile("fence.acq_rel.gpu;" ::: "memory");
        if (lane == 0) asm volatile("red.relaxed.gpu.global.add.u32 [%0],1;" ::"l"(fb + (qe.y & 63) * 4 + ((qe.y >> 6) & 3)) : "memory");
    }
}

constexpr int EXPORT_WARP = 30;
__device__ __forceinline__ uint2 lock64(uint32_t a) {
    uint2 r;
    asm volatile("{.reg .b64 y; atom.shared.exch.b64 y,[%2],0xffffffffffffffff; mov.b64 {%0,%1},y;}" : "=r"(r.x), "=r"(r.y) : "r"(a) : "memory");
    return r;
}

__device__ __forceinline__ void stage3(const Params& p, unsigned char* sm, int g, int o) {
    const int warp = warp_id(), lane = lane_id();
    constexpr uint32_t sb = SB;
    if (threadIdx.x < 64) ((uint32_t*)(sm + SM_AUX + AUX_DUMMY))[threadIdx.x] = ~0u;
    for (int i = (g * NO + o) * 1024 + threadIdx.x; i < NO * (int)SO / 2; i += N3 * 1024) ((uint4*)g_agg)[i] = make_uint4(0, 0, 0, 0);
    __syncthreads();
    if (threadIdx.x == 0) asm volatile("red.release.gpu.global.add.u32 [%0],1;" ::"l"(&g_sync[SY_ZERO]) : "memory");
    const int t0 = p.pairs * 2 * STEP + (g * NO + o) * 1024 + threadIdx.x;
    static_assert(2 * STEP <= N3 * 1024, "remainder");
    if (t0 - lane < p.T) {
        const int t = min(t0, p.T - 1);
        const uint2 v = __ldg(p.m + p.idx_in[t]);
        wait_zeroed();
        if (t0 < p.T) red_agg(p.idx_out[t], v, dup_bf16(cos_any(rbf16(bf_lo(p.freq[0]) * bf_lo(p.angle[t])))));
        __syncwarp();
    }
    constexpr int NCW = 20, STEPS = IG / 4;
    uint32_t* const fb = flag_base(sm, g, FL_GO2);
    if (warp == 31) {
        poller<NCW, FL_GO3>(sm, g, (XO + o * XSEG) >> 12, (XO + XG) >> 12, p.units, p.units - 2 * N1, [&] {
            constexpr int H = (SO / 2 + 7) & ~7;
            const int e0 = (o * SO + g * H) & ~7, n = min(H + 8, p.E - e0) & ~7;
            if (n > 0 && elect_one()) {
                asm volatile("cp.async.bulk.prefetch.L2.global [%0],%1;" ::"l"(g_agg + e0), "r"(n * 8) : "memory");
                asm volatile("cp.async.bulk.prefetch.L2.global [%0],%1;" ::"l"(p.dist + e0), "r"(n * 2) : "memory");
            }
            __syncwarp();
        });
    } else if (warp < NCW) {
        const uint32_t dummy = sb + SM_AUX + AUX_DUMMY + lane * 8, r0 = (lane & 7) * 2;
        const uint32_t vlane = slot_v(0) + ring_off(0, o * VSEG) + lane * 16, xlane = ring_off(0, XO + o * XSEG) + lane * 4;
        const uint32_t clane = ring_off(0, XO + XG + o * IG) + (lane >> 3) * 4;
        for (int t = warp; t < p.units; t += NCW) {
            uint2 qe;
            next_unit<true>(sb + SM_AUX, warp, t, NCW, qe);
            const uint32_t tag = qe.x >> 31, ab = slot_a((qe.x >> 16) & 0xff);
            const uint4* vp = (const uint4*)(g_ring + (((qe.x >> 24) & 0x7f) * (PV * 8192) + vlane + (((qe.x >> (o >> 1)) & 1) << 12)));
            const uint32_t* xp = (const uint32_t*)(g_ring + (ab + xlane + ((qe.x >> 2) & 0x1000)));
            const uint32_t* cp = (const uint32_t*)(g_ring + (ab + clane + ((qe.x >> 3) & 0x1000)));
            uint4 v[STEPS]; uint32_t x[STEPS];
            const uint32_t cn = __ldcg(cp);
#pragma unroll
            for (int j = 0; j < STEPS; j++) x[j] = __ldcg(xp + j * 32);
#pragma unroll
            for (int j = 0; j < STEPS; j++) v[j] = ld128(vp + j * 32);
            for (int spins = 0;; spins++) {
                uint32_t bad = 0;
#pragma unroll
                for (int j = 0; j < STEPS; j++) bad |= v[j].x ^ tag;
                if (!__any_sync(0xffffffffu, bad & 1)) break;
                if (spins > (1 << 22)) __trap();
#pragma unroll
                for (int j = 0; j < STEPS; j++) v[j] = ld128(vp + j * 32);
            }
            uint32_t ad[2 * STEPS], dep = cn;
#pragma unroll
            for (int j = 0; j < STEPS; j++) {
                const uint32_t c = (cn >> (8 * j)) & 0xff;
                ad[2 * j] = r0 < c ? sb + (x[j] & 0xffff) * 8 : dummy;
                ad[2 * j + 1] = r0 + 1 < c ? sb + (x[j] >> 16) * 8 : dummy;
                dep ^= x[j];
            }
            if (lane == 0) asm volatile("red.relaxed.gpu.global.add.u32 [%0],%1;" ::"l"(fb + (qe.y & 63) * 4 + (((qe.y >> 6) + DV) & 3)), "r"(1 + (dep & p.zero)) : "memory");
            uint32_t pend = 0;
#pragma unroll
            for (int j0 = 0; j0 < 2 * STEPS; j0 += 4) {
                uint2 t[4];
#pragma unroll
                for (int j = 0; j < 4; j++) t[j] = lock64(ad[j0 + j]);
#pragma unroll
                for (int j = 0; j < 4; j++) {
                    const int jj = j0 + j;
                    const uint32_t vx = (jj & 1) ? v[jj / 2].z : v[jj / 2].x, vy = (jj & 1) ? v[jj / 2].w : v[jj / 2].y;
                    asm volatile("{.reg .pred p,q; setp.ne.u32 p,%4,0xffffffff; @p st.shared.v2.u32 [%1],{%2,%3}; setp.ne.and.u32 q,%1,%5,!p; @q or.b32 %0,%0,%6;}"
                                 : "+r"(pend) : "r"(ad[jj]), "r"(hadd2(t[j].x, vx)), "r"(hadd2(t[j].y, vy)), "r"(t[j].x), "r"(dummy), "r"(1u << jj) : "memory");
                }
            }
            while (__any_sync(0xffffffffu, pend)) {
                uint32_t a = dummy, vx = 0, vy = 0;
#pragma unroll
                for (int jj = 2 * STEPS - 1; jj >= 0; jj--)
                    if (pend & (1u << jj)) { a = ad[jj]; vx = (jj & 1) ? v[jj / 2].z : v[jj / 2].x; vy = (jj & 1) ? v[jj / 2].w : v[jj / 2].y; }
                const uint2 t = lock64(a);
                asm volatile("{.reg .pred p; setp.ne.u32 p,%4,0xffffffff; @p st.shared.v2.u32 [%1],{%2,%3}; @p and.b32 %0,%0,%5;}"
                             : "+r"(pend) : "r"(a), "r"(hadd2(t.x, vx)), "r"(hadd2(t.y, vy)), "r"(t.x), "r"(pend - 1) : "memory");
            }
        }
    }
    static_assert(NCW <= EXPORT_WARP, "export warp");
    if (warp != EXPORT_WARP) {
        asm volatile("fence.proxy.async.shared::cta;" ::: "memory");
        bar_arrive(1, 1024);
    }
}

__device__ __forceinline__ void mma_edge(float (&c)[4], uint32_t p01, uint32_t q01, uint32_t p23, uint32_t q23, uint2 b) {
    asm("mma.sync.aligned.m16n8k16.row.col.f32.bf16.bf16.f32 {%0,%1,%2,%3},{%4,%5,%6,%7},{%8,%9},{%0,%1,%2,%3};"
        : "+f"(c[0]), "+f"(c[1]), "+f"(c[2]), "+f"(c[3]) : "r"(p01), "r"(q01), "r"(p23), "r"(q23), "r"(b.x), "r"(b.y));
}
__device__ __forceinline__ uint2 b_frag(const uint16_t* w, int j0) {
    int lane; asm("mov.u32 %0,%%laneid;" : "=r"(lane));
    const int j = j0 + ((lane >> 2) & 1);
    const uint2 v = make_uint2(w[j] | ((uint32_t)w[4 + j] << 16), w[8 + j] | ((uint32_t)w[12 + j] << 16));
    return (lane & 3) == (lane >> 3) ? v : make_uint2(0, 0);
}
__device__ __forceinline__ void edge_gates(const uint16_t* w, uint32_t d2, uint4& sp, uint4& gp) {
    uint32_t rb[2][4];
#pragma unroll
    for (int k = 0; k < 2; k++)
#pragma unroll
        for (int r = 0; r < 4; r++) {
            uint32_t x; asm("sub.rn.bf16x2 %0,%1,%2;" : "=r"(x) : "r"(__byte_perm(d2, 0, k ? 0x3232 : 0x1010)), "r"(((const uint32_t*)w)[48 + r]));
            const uint32_t t = hmul2(hmul2(x, x), 0xc120c120u);
            rb[k][r] = pack2(__expf(bf_lo(t)), __expf(bf_hi(t)));
        }
    uint32_t o[4][2];
#pragma unroll
    for (int n = 0; n < 4; n++) {
        float c[4] = {};
        mma_edge(c, rb[0][0], rb[1][0], rb[0][1], rb[1][1], b_frag(w + (n >> 1) * 32, (n & 1) * 2));
        mma_edge(c, rb[0][2], rb[1][2], rb[0][3], rb[1][3], b_frag(w + (n >> 1) * 32 + 16, (n & 1) * 2));
        o[n][0] = pack2(c[0], c[1]); o[n][1] = pack2(c[2], c[3]);
    }
    gp = make_uint4(o[0][0], o[1][0], o[0][1], o[1][1]);
    sp = make_uint4(o[2][0], o[3][0], o[2][1], o[3][1]);
}
__device__ __forceinline__ uint4 edge_finish(const uint16_t* w, uint4 a, uint4 sp, uint4 gp, uint4 mv) {
    float t0[4] = {}, t1[4] = {}, u0[4] = {}, u1[4] = {};
    mma_edge(t0, a.x, a.z, a.y, a.w, b_frag(w + 64, 0));
    mma_edge(t1, a.x, a.z, a.y, a.w, b_frag(w + 64, 2));
    const uint32_t p01 = pack2(t0[0] * bf_lo(sp.x), t0[1] * bf_hi(sp.x)), p23 = pack2(t1[0] * bf_lo(sp.y), t1[1] * bf_hi(sp.y));
    const uint32_t q01 = pack2(t0[2] * bf_lo(sp.z), t0[3] * bf_hi(sp.z)), q23 = pack2(t1[2] * bf_lo(sp.w), t1[3] * bf_hi(sp.w));
    mma_edge(u0, p01, q01, p23, q23, b_frag(w + 80, 0));
    mma_edge(u1, p01, q01, p23, q23, b_frag(w + 80, 2));
    return make_uint4(hadd2(mv.x, hmul2(pack2(u0[0], u0[1]), gp.x)), hadd2(mv.y, hmul2(pack2(u1[0], u1[1]), gp.y)),
                      hadd2(mv.z, hmul2(pack2(u0[2], u0[3]), gp.z)), hadd2(mv.w, hmul2(pack2(u1[2], u1[3]), gp.w)));
}

__device__ __forceinline__ void finish(const Params& p, unsigned char* sm) {
    __syncwarp();
    const int b = blockIdx.x, tid = threadIdx.x;
    const int role = ((const volatile uint32_t*)(sm + SM_AUX + AUX_MISC))[2];
    const uint16_t* w = (const uint16_t*)(sm + SM_AUX + AUX_W);
    if (role != 3) {
        __syncthreads();
        if (tid == 0) asm volatile("red.release.gpu.global.add.u32 [%0],1;" ::"l"(&g_sync[SY_END]) : "memory");
    }
    constexpr int EP = 3, es = NCTA * 1024;
    static_assert(EP * es * 2 >= E_CAP, "epilogue");
    uint4 sg[2 * EP];
    const int e0 = b * 1024 + tid, np = p.E / 2;
#pragma unroll
    for (int k = 0; k < EP; k++) sg[2 * k].x = __ldg((const uint32_t*)p.dist + min(e0 + k * es, np - 1));
#pragma unroll
    for (int k = 0; k < EP; k++) edge_gates(w, sg[2 * k].x, sg[2 * k], sg[2 * k + 1]);
    uint4 mv[EP];
#pragma unroll
    for (int k = 0; k < EP; k++) mv[k] = __ldg((const uint4*)p.m + min(e0 + k * es, np - 1));
    if (role == 3) {
        if (warp_id() == EXPORT_WARP) {
            const int rank = ((const volatile uint32_t*)(sm + SM_AUX + AUX_MISC))[3], o = rank & 255;
            static_assert(SO % 6 == 0, "export");
            wait_zeroed();
            __syncwarp();
            bar_sync(1, 1024);
            if (elect_one()) {
                asm volatile("fence.proxy.async.global;" ::: "memory");
#pragma unroll
                for (int k = 0; k < 3; k++)
                    asm volatile("cp.reduce.async.bulk.global.shared::cta.bulk_group.add.noftz.bf16 [%0],[%1],%2;" ::"l"(g_agg + o * SO + k * (SO / 3)), "r"(SB + k * (SO / 3) * 8), "n"(SO / 3 * 8) : "memory");
                asm volatile("cp.async.bulk.commit_group;" ::: "memory");
                asm volatile("cp.async.bulk.wait_group 0;" ::: "memory");
            }
            __syncwarp();
            bar_arrive(2, 1024);
            if (elect_one()) asm volatile("red.release.gpu.global.add.u32 [%0],1;" ::"l"(&g_sync[SY_END]) : "memory");
            __syncwarp();
        } else bar_sync(2, 1024);
    }
    uint4* const stash = (uint4*)sm + tid;
#pragma unroll
    for (int k = 0; k < EP; k++) { stash[(3 * k) * 1024] = sg[2 * k]; stash[(3 * k + 1) * 1024] = sg[2 * k + 1]; stash[(3 * k + 2) * 1024] = mv[k]; }
    if (tid == 0) {
        wait_flag(&g_sync[SY_END], NCTA);
        asm volatile("fence.acquire.gpu;" ::: "memory");
    }
    __syncthreads();
    uint4 av[EP];
#pragma unroll
    for (int k = 0; k < EP; k++) av[k] = __ldcg((const uint4*)g_agg + min(e0 + k * es, np - 1));
#pragma unroll
    for (int k = 0; k < EP; k++) {
        const uint4 o = edge_finish(w, av[k], stash[(3 * k) * 1024], stash[(3 * k + 1) * 1024], stash[(3 * k + 2) * 1024]);
        if (e0 + k * es < np) ((uint4*)p.out)[e0 + k * es] = o;
    }
    if (b == 0 && tid < 512) ((uint4*)(g_ring + slot_v(KV)))[tid] = make_uint4(0, 0, 0, 0);
    if (tid == 0) {
        g_info[b] = make_uint2(0, 0);
        if (atomicAdd(&g_sync[SY_EXIT], 1) == NCTA - 1)
            g_sync[SY_ZERO] = g_sync[SY_END] = g_sync[SY_EXIT] = g_sync[SY_WORK] = g_sync[SY_LOG] = g_sync[SY_LOG + 1] = 0;
    }
}

__global__ void __launch_bounds__(1024, 1) main_kernel(const __grid_constant__ Params p) {
    extern __shared__ __align__(128) unsigned char sm[];
    const int b = blockIdx.x, tid = threadIdx.x, warp = tid >> 5;
    if ((uint32_t)__cvta_generic_to_shared(sm) != SB) __trap();
    uint32_t* s_misc = (uint32_t*)(sm + SM_AUX + AUX_MISC);
    if (tid == 0) s_misc[0] = s_misc[4] = s_misc[5] = 0;
    __syncthreads();
    if ((tid & 31) == 0) {
        const int sl = b * 2 + (warp >> 4), j = warp & 15;
        if (warp == 31) s_misc[1] = upper_is_near(g_probe + (b & 127) * 32);
        else if (sl < NSL && j < (sl < KA ? PA : sl < KA + KV ? PV : 1) &&
                 upper_is_near(g_ring + (sl < KA ? slot_a(sl) : slot_v(sl - KA)) + j * 8192 + 4064))
            atomicOr(&s_misc[0], 1u << warp);
    }
    __syncwarp();
    __syncthreads();
    uint32_t me; asm("mov.u32 %0,%%smid;" : "=r"(me));
    me = 0x8000u | (s_misc[1] << 14) | (me & 0x3fff);
    if (tid == 0) {
        const u64 v = (u64)(s_misc[0] ^ (s_misc[1] ? ~0u : 0u)) | ((u64)me << 32);
        asm volatile("st.release.gpu.global.u64 [%0],%1;" ::"l"(&g_info[b]), "l"(v) : "memory");
    }
    for (int i = tid; i < (SM_AUX + AUX_CLS) / 16; i += 1024) ((uint4*)sm)[i] = make_uint4(0, 0, 0, 0);
    uint16_t* w = (uint16_t*)(sm + SM_AUX + AUX_W);
    if (tid < 160) {
        u64 v = 0; int spins = 0;
        while (tid < NCTA && !(v >> 32)) {
            asm volatile("ld.acquire.gpu.global.u64 %0,[%1];" : "=l"(v) : "l"(&g_info[tid]) : "memory");
            if (++spins > (1 << 22)) __trap();
        }
        __syncwarp();
        if (tid < NCTA) ((uint32_t*)(sm + SM_AUX + AUX_CLS))[tid] = (uint32_t)v;
        const uint32_t o = v >> 32;
        const uint32_t c = __reduce_add_sync(0xffffffffu, tid < NCTA ? 1u << (8 * ((o & 1) | ((o >> 13) & 2))) : 0u);
        const uint32_t r = __popc(__ballot_sync(0xffffffffu, tid < NCTA && ((o ^ me) & 0x4001) == 0 && (o > me || (o == me && tid > b))));
        if ((tid & 31) == 0) { atomicAdd(&s_misc[4], c); atomicAdd(&s_misc[5], r); }
    } else if (tid >= 256 && tid < 256 + 104) {
        const int j = tid - 256;
        w[j] = j < 32 ? p.w_rbf[j] : j < 64 ? p.w_sbf[j - 32] : j < 80 ? p.w_down[j - 64] : j < 96 ? p.w_up[j - 80] : p.centers[j - 96];
    }
    __syncthreads();
    int role, rank;
    {
        const uint32_t cnt = s_misc[4], cl = (me & 1) | ((me >> 13) & 2);
        rank = s_misc[5];
        const int c2 = (rank + 1) * IG / NO;
        if (__vminu4(cnt, NO * 0x01010101u) != NO * 0x01010101u) {
            role = b < N2 ? 2 : b < N2 + N3 ? 3 : 1;
            const int r = role == 2 ? b : b - N2;
            rank = role == 1 ? b - N2 - N3 : (r >> 1) | ((r & 1) << 8);
        } else if (rank < NO && (me & 1)) { role = 3; rank |= (cl >> 1) << 8; }
        else if (rank < NO && c2 != rank * IG / NO) { role = 2; rank = (c2 - 1) | ((cl >> 1) << 8); }
        else {
            role = 1;
            rank -= (me & 1) ? NO : min(c2, IG);
            for (uint32_t c = 0; c < cl; c++) rank += ((cnt >> (8 * c)) & 0xff) - ((c & 1) ? NO : IG);
        }
        if (tid == 0) { s_misc[2] = role; s_misc[3] = rank; }
    }
    if (role == 1) stage1(p, sm, rank);
    else if (role == 2) stage2(p, sm, rank >> 8, rank & 255);
    else stage3(p, sm, rank >> 8, rank & 255);
    finish(p, sm);
}

__global__ void generic_scatter(const __grid_constant__ Params p) {
    const float f = bf_lo(p.freq[0]);
    for (int t = blockIdx.x * blockDim.x + threadIdx.x; t < p.T; t += gridDim.x * blockDim.x) {
        const uint2 v = __ldg(p.m + p.idx_in[t]);
        const uint32_t c2 = dup_bf16(cos_any(rbf16(f * bf_lo(p.angle[t]))));
        asm volatile("red.global.add.noftz.v2.bf16x2 [%0],{%1,%2};" ::"l"(p.out + p.idx_out[t]), "r"(hmul2(v.x, c2)), "r"(hmul2(v.y, c2)) : "memory");
    }
}
__global__ void __launch_bounds__(256) generic_finish(const __grid_constant__ Params p) {
    __shared__ __align__(16) uint16_t w[104];
    const int j = threadIdx.x, e = blockIdx.x * blockDim.x + j, ec = min(e, p.E - 1);
    if (j < 104) w[j] = j < 32 ? p.w_rbf[j] : j < 64 ? p.w_sbf[j - 32] : j < 80 ? p.w_down[j - 64] : j < 96 ? p.w_up[j - 80] : p.centers[j - 96];
    const uint2 a = p.out[ec], mv = p.m[ec];
    __syncthreads();
    uint4 s0, s1;
    edge_gates(w, p.dist[ec] * 0x10001u, s0, s1);
    const uint4 o = edge_finish(w, make_uint4(a.x, a.y, a.x, a.y), s0, s1, make_uint4(mv.x, mv.y, mv.x, mv.y));
    if (e < p.E) p.out[e] = make_uint2(o.x, o.y);
}

extern "C" void kernel_launch(void* const* d_in, const int* in_sizes, int n_in, void* d_out, int out_size) {
    static int nsm = 0;
    if (!nsm) {
        cudaDeviceGetAttribute(&nsm, cudaDevAttrMultiProcessorCount, 0);
        cudaFuncSetAttribute(main_kernel, cudaFuncAttributeMaxDynamicSharedMemorySize, SMEM_BYTES);
    }
    Params p;
    p.m = (const uint2*)d_in[0]; p.idx_in = (const int*)d_in[1]; p.idx_out = (const int*)d_in[2];
    p.angle = (const uint16_t*)d_in[4]; p.freq = (const uint16_t*)d_in[6];
    p.dist = (const uint16_t*)d_in[3]; p.centers = (const uint16_t*)d_in[5]; p.w_rbf = (const uint16_t*)d_in[7];
    p.w_sbf = (const uint16_t*)d_in[8]; p.w_down = (const uint16_t*)d_in[9]; p.w_up = (const uint16_t*)d_in[10];
    p.out = (uint2*)d_out;
    p.E = in_sizes[3]; p.T = in_sizes[1];
    p.zero = 0;
    p.pairs = p.T / (2 * STEP); p.units = p.pairs + (NR / 2 + 1) * N1;
    bool fast = nsm >= NCTA && p.E <= E_CAP && p.E >= 8 && p.E % 2 == 0 && p.pairs >= 2 * N1 && p.units < 0xff00;
    static cudaTextureObject_t tex[3];
    static const void* tex_ptr[3];
    static int tex_n[3];
    for (int k = 0; k < 3 && fast; k++) {
        void* ptr = d_in[k == 2 ? 4 : 1 + k];
        if (tex_ptr[k] == ptr && tex_n[k] == p.T) continue;
        cudaResourceDesc rd = {};
        rd.resType = cudaResourceTypeLinear;
        rd.res.linear.devPtr = ptr;
        rd.res.linear.desc = k == 2 ? cudaCreateChannelDesc<uint2>() : cudaCreateChannelDesc<uint4>();
        rd.res.linear.sizeInBytes = (size_t)(p.T / 4) * (k == 2 ? 8 : 16);
        cudaTextureDesc td = {};
        td.readMode = cudaReadModeElementType;
        if (cudaCreateTextureObject(&tex[k], &rd, &td, nullptr) == cudaSuccess) { tex_ptr[k] = ptr; tex_n[k] = p.T; }
        else { cudaGetLastError(); tex_ptr[k] = nullptr; fast = false; }
    }
    p.tin = tex[0]; p.tout = tex[1]; p.tang = tex[2];
    if (!fast) {
        cudaMemsetAsync(d_out, 0, (size_t)p.E * 8);
        generic_scatter<<<nsm * 8, 256>>>(p);
        generic_finish<<<(p.E + 255) / 256, 256>>>(p);
        return;
    }
    void* args[] = {&p};
    cudaLaunchCooperativeKernel((const void*)main_kernel, dim3(NCTA), dim3(1024), args, SMEM_BYTES, cudaStreamPerThread);
}
```

```cpp
#include <cuda_runtime.h>
#include <cuda_bf16.h>
#include <stdint.h>

typedef unsigned long long u64;
constexpr uint32_t magic_of(uint32_t d) { return (uint32_t)(((1ull << 32) + d - 1) / d); }
constexpr uint32_t slice_of(uint32_t total, uint32_t n) {
    uint32_t d = ((total + n - 1) / n + 1) & ~1u;
    while (!((uint64_t)(n * d - 1) * magic_of(d) < ((uint64_t)n << 32))) d += 2;
    return d;
}
constexpr int E_CAP = 800000;
constexpr int NI = 32, NO = 28, NG = 2, IG = NI / NG;
constexpr uint32_t SI = slice_of(E_CAP, NI), SO = slice_of(E_CAP, NO);
constexpr uint32_t MI = magic_of(SI), MO = magic_of(SO);
constexpr int NCTA = 132, N2 = NI, N3 = NO * NG, N1 = NCTA - N2 - N3;
constexpr int C = 16, GB = NO * IG;
constexpr int NP = 5;
constexpr int NW = 28, STEP = NW * 256;
constexpr int NR = 4, LOGCAP = 8192, NCH = N1 * NW * NR * 8, KMAX = 4000;
static_assert(NR % 2 == 0 && NR >= 2 && NR <= 4 && NO % 4 == 0 && IG == 16, "shape");

constexpr int DA = 3, DS = 2, DV = 2, KA = DA * N1, KV = DV * N1, NSL = KA + KV + 1;
constexpr int ASEG = NO * C * 4, XSEG = IG * C * 2, VSEG = IG * C * 8;
constexpr int AG = IG * ASEG, XG = NO * XSEG, XO = IG / 2 * 4096, AXG = XO + XG + GB;
constexpr int PA = (AXG + 4095) / 4096, PV = NO * VSEG / 4096;
static_assert(2 * ASEG <= 4096 && AG == 2 * XG && (XO + XG) / 4096 == (AXG - 1) / 4096 && PA <= 15 && PV <= 14, "layout");
static_assert(DS >= DA - DV && DS <= DA && KA <= 256 && KV <= 128 && NSL <= 2 * NCTA && N1 <= 64, "ring");

constexpr uint32_t SB = 1024;
constexpr int SM_CNT = 0, SM_CB = NG * GB * 4, SM_LC = SM_CB + 2 * GB, SM_X = SM_LC + 256, SM_A = SM_X + NP * XG,
              SM_S1_END = SM_A + NP * AG;
constexpr int SM_AUX = SO * 8 + 512, QN = 256;
constexpr int AUX_Q = 0, AUX_PROG = QN * 8, AUX_CLS = AUX_PROG + 128, AUX_MISC = AUX_CLS + 576, AUX_DUMMY = AUX_MISC + 32,
              AUX_W = AUX_DUMMY + 256, AUX_END = AUX_W + 208;
constexpr int SMEM_BYTES = SM_AUX + AUX_END;
static_assert(SM_S1_END + 256 + NW * 256 <= SM_AUX && SMEM_BYTES <= 232448 && SM_X % 128 == 0 && AUX_W % 16 == 0, "smem");

__device__ __align__(8192) unsigned char g_ring[(size_t)(KA * PA + KV * PV + 1) * 8192];
__device__ __align__(8192) unsigned char g_probe[8192];
__device__ uint2 g_log[N1 * NW * LOGCAP];
__device__ uint32_t g_chunks[NCH];
__device__ __align__(128) uint2 g_agg[NO * SO];
__device__ uint2 g_info[NCTA];
__device__ __align__(128) uint32_t g_sync[160];
constexpr int SY_ZERO = 0, SY_END = 32, SY_EXIT = 64, SY_WORK = 96, SY_LOG = 128;
constexpr int FL_GO2 = 0, FL_GO3 = 1;
constexpr uint32_t FL_DATA = 0x10000;

__device__ __forceinline__ int lane_id() { int v; asm volatile("mov.u32 %0,%%laneid;" : "=r"(v)); return v; }
__device__ __forceinline__ int warp_id() { int v; asm volatile("mov.u32 %0,%%tid.x;" : "=r"(v)); return __shfl_sync(0xffffffffu, v >> 5, 0); }
__device__ __forceinline__ float bf_lo(uint32_t v) { return __uint_as_float(v << 16); }
__device__ __forceinline__ float bf_hi(uint32_t v) { return __uint_as_float(v & 0xffff0000u); }
__device__ __forceinline__ float rbf16(float x) { return __bfloat162float(__float2bfloat16_rn(x)); }
__device__ __forceinline__ uint32_t hmul2(uint32_t a, uint32_t b) {
    uint32_t d; asm("mul.rn.bf16x2 %0,%1,%2;" : "=r"(d) : "r"(a), "r"(b)); return d;
}
__device__ __forceinline__ uint32_t hadd2(uint32_t a, uint32_t b) {
    uint32_t d; asm("add.rn.bf16x2 %0,%1,%2;" : "=r"(d) : "r"(a), "r"(b)); return d;
}
__device__ __forceinline__ uint32_t dup_bf16(float x) {
    uint32_t d; asm("cvt.rn.bf16x2.f32 %0,%1,%1;" : "=r"(d) : "f"(x)); return d;
}
__device__ __forceinline__ uint32_t pack2(float lo, float hi) {
    uint32_t d; asm("cvt.rn.bf16x2.f32 %0,%2,%1;" : "=r"(d) : "f"(lo), "f"(hi)); return d;
}
__device__ __noinline__ float cos_slow(float x) { return cosf(x); }
__device__ __forceinline__ float cos_any(float x) { return fabsf(x) < 32.f ? __cosf(x) : cos_slow(x); }
__device__ __forceinline__ void bar_sync(int id, int n) { asm volatile("barrier.sync.aligned %0,%1;" ::"r"(id), "r"(n) : "memory"); }
__device__ __forceinline__ void bar_arrive(int id, int n) { asm volatile("barrier.arrive.aligned %0,%1;" ::"r"(id), "r"(n) : "memory"); }
__device__ __forceinline__ uint32_t ld_relaxed(const uint32_t* p) {
    uint32_t v; asm volatile("ld.relaxed.gpu.global.u32 %0,[%1];" : "=r"(v) : "l"(p) : "memory"); return v;
}
__device__ __forceinline__ void st128(void* p, uint4 v) {
    asm volatile("{.reg .b64 a,b; .reg .b128 q; mov.b64 a,{%1,%2}; mov.b64 b,{%3,%4}; mov.b128 q,{a,b}; st.relaxed.gpu.global.b128 [%0],q;}" ::"l"(p), "r"(v.x), "r"(v.y), "r"(v.z), "r"(v.w) : "memory");
}
__device__ __forceinline__ uint4 ld128(const void* p) {
    uint4 v;
    asm volatile("{.reg .b64 a,b; .reg .b128 q; ld.relaxed.gpu.global.b128 q,[%4]; mov.b128 {a,b},q; mov.b64 {%0,%1},a; mov.b64 {%2,%3},b;}" : "=r"(v.x), "=r"(v.y), "=r"(v.z), "=r"(v.w) : "l"(p) : "memory");
    return v;
}
__device__ __forceinline__ void wait_flag(const uint32_t* p, uint32_t want) {
    int spins = 0;
    while ((ld_relaxed(p) & 0xffff) < want) {
        __nanosleep(100);
        if (++spins > (1 << 22)) __trap();
    }
}
__device__ __forceinline__ uint32_t slot_a(int s) { return s * (PA * 8192); }
__device__ __forceinline__ uint32_t slot_v(int s) { return KA * PA * 8192 + s * (PV * 8192); }
__device__ __forceinline__ uint32_t ring_off(uint32_t clsg, uint32_t off) {
    return ((off >> 12) << 13) + (((clsg >> (off >> 12)) & 1) << 12) + (off & 4095);
}
__device__ __forceinline__ uint32_t cls_of(const unsigned char* sm, int s, int g) {
    return ((const uint16_t*)(sm + SM_AUX + AUX_CLS))[s] ^ (g ? ~0u : 0u);
}
__device__ __forceinline__ uint32_t flag_idx(const unsigned char* sm, int g, int type, int q) {
    return ring_off(cls_of(sm, NSL - 1, g), type * 1024 + q * 8) / 4;
}
__device__ __forceinline__ uint32_t* flags() { return (uint32_t*)(g_ring + slot_v(KV)); }
__device__ __forceinline__ uint32_t arrivals(int type, uint32_t k) {
    static_assert(DV == 2, "flag ring");
    return type == FL_GO3 ? IG * ((k >> 1) + 1) : NO * (k >> 1);
}
__device__ __forceinline__ bool elect_one() {
    uint32_t r; asm volatile("{.reg .pred p; elect.sync _|p,0xffffffff; selp.u32 %0,1,0,p;}" : "=r"(r)); return r;
}
template <int NCW, int TYPE, class F>
__device__ __forceinline__ void poller(const unsigned char* sm, int g, int blk0, int blk1, int units, int hook_at, F hook) {
    const int lane = lane_id();
    constexpr uint32_t aux = SB + SM_AUX;
    constexpr int DR = TYPE == FL_GO2 ? DS : DA;
    const uint32_t lt = (1u << lane) - 1;
    uint32_t ea[2][DR], ev[2][DV], k[2] = {0, 0}, want[2], v[2], fin[2], fout[2];
#pragma unroll
    for (int j = 0; j < 2; j++) {
        const int q = min(lane + j * 32, N1 - 1);
#pragma unroll
        for (int d = 0; d < DR; d++) {
            const uint32_t sa = q + d * N1, ca = cls_of(sm, sa, g);
            ea[j][d] = (((ca >> blk0) & 1) << 14) | (((ca >> blk1) & 1) << 15) | (sa << 16);
        }
#pragma unroll
        for (int d = 0; d < DV; d++) ev[j][d] = (cls_of(sm, KA + q + d * N1, g) & 0x3fff) | ((q + d * N1) << 24);
        want[j] = lane + j * 32 < N1 ? FL_DATA + arrivals(TYPE, 0) : ~0u;
        v[j] = 0;
        fin[j] = flag_idx(sm, g, TYPE, q); fout[j] = flag_idx(sm, g, TYPE ^ 1, q);
    }
    int tail = 0, check = min(min(QN - N1, hook_at), units), spins = 0;
    while (true) {
        bool hit[2]; uint32_t bal[2];
#pragma unroll
        for (int j = 0; j < 2; j++) {
            hit[j] = v[j] >= want[j] && (uint16_t)v[j] >= (uint16_t)want[j];
            bal[j] = __ballot_sync(0xffffffffu, hit[j]);
        }
        if (bal[0] | bal[1]) {
            asm volatile("fence.acquire.gpu;" ::: "memory");
            if (TYPE == FL_GO2) asm volatile("fence.proxy.async.global;" ::: "memory");
            asm volatile("fence.acq_rel.cta;" ::: "memory");
            spins = 0;
        } else if (++spins > (1 << 22)) __trap();
#pragma unroll
        for (int j = 0; j < 2; j++) {
            const uint32_t pos = tail + __popc(bal[j] & lt);
            const uint32_t hi = fout[j] | (k[j] & 1) | (k[j] < DV ? 0x8000 : 0) | ((pos + 1) << 16);
            asm volatile("{.reg .pred p; .reg .b64 q; setp.ne.u32 p,%3,0; mov.b64 q,{%1,%2}; @p st.relaxed.cta.shared.u64 [%0],q;}"
                         ::"r"(aux + AUX_Q + (pos % QN) * 8), "r"(ea[j][0] | ev[j][0]), "r"(hi), "r"((uint32_t)hit[j]) : "memory");
            tail += __popc(bal[j]);
            k[j] += hit[j];
        }
#pragma unroll
        for (int j = 0; j < 2; j++) v[j] = ld_relaxed(flags() + (fin[j] | (k[j] & 1)));
#pragma unroll
        for (int j = 0; j < 2; j++) {
            const uint32_t a0 = ea[j][0], v0 = ev[j][0] ^ 0x80000000u;
#pragma unroll
            for (int d = 0; d < DR; d++) ea[j][d] = hit[j] ? (d + 1 < DR ? ea[j][(d + 1) % DR] : a0) : ea[j][d];
#pragma unroll
            for (int d = 0; d < DV; d++) ev[j][d] = hit[j] ? (d + 1 < DV ? ev[j][(d + 1) % DV] : v0) : ev[j][d];
            want[j] = hit[j] ? ((k[j] >> 1) + 1) * FL_DATA + arrivals(TYPE, k[j]) : want[j];
        }
        if (tail >= check) {
            if (tail >= units) break;
            if (tail >= hook_at) { hook(); hook_at = 0x7fffffff; }
            int limit;
            do {
                int prog; asm volatile("ld.volatile.shared.u32 %0,[%1];" : "=r"(prog) : "r"(aux + AUX_PROG + min(lane, NCW - 1) * 4) : "memory");
                limit = __reduce_min_sync(0xffffffffu, prog) + QN - N1;
            } while (tail > limit);
            check = min(min(limit, hook_at), units);
        }
    }
}
template <bool BLOCK>
__device__ __forceinline__ bool next_unit(uint32_t aux, int warp, int t, int step, uint2& e) {
    u64 v;
    while (true) {
        asm volatile("ld.acquire.cta.shared.u64 %0,[%1];" : "=l"(v) : "r"(aux + AUX_Q + (t % QN) * 8) : "memory");
        if (__all_sync(0xffffffffu, (int)(v >> 48) == t + 1)) break;
        if (!BLOCK) return false;
        __nanosleep(40);
    }
    if (((t + step) ^ t) & 64) asm volatile("st.volatile.shared.u32 [%0],%1;" ::"r"(aux + AUX_PROG + warp * 4), "r"(t + step) : "memory");
    e = make_uint2((uint32_t)v, (uint32_t)(v >> 32) & 0xffff);
    return true;
}
__device__ __forceinline__ int upper_is_near(unsigned char* q) {
    ((uint4*)q)[0] = ((uint4*)q)[1] = ((uint4*)(q + 4096))[0] = ((uint4*)(q + 4096))[1] = make_uint4(0, 0, 0, 0);
    uint32_t best[2] = {~0u, ~0u};
#pragma unroll
    for (int r = 0; r < 4; r++) {
        uint32_t t0, t1, v;
        asm volatile("mov.u32 %0,%%clock;" : "=r"(t0)::"memory");
        asm volatile("atom.global.exch.b32 %0,[%1],0;" : "=r"(v) : "l"(q + (r & 1) * 4096) : "memory");
        asm volatile("{.reg .pred p; setp.eq.u32 p,%1,0xffffffff; @p trap; mov.u32 %0,%%clock;}" : "=r"(t1) : "r"(v) : "memory");
        best[r & 1] = min(best[r & 1], t1 - t0);
    }
    return best[1] < best[0];
}

struct Params {
    const uint2* m; const int* idx_in; const int* idx_out; const uint16_t* angle; const uint16_t* freq;
    const uint16_t *dist, *centers, *w_rbf, *w_sbf, *w_down, *w_up; uint2* out;
    int E, T, pairs, units;
    uint32_t zero;
    cudaTextureObject_t tin, tout, tang;
};

__device__ __forceinline__ void red_agg(uint32_t out, uint2 v, uint32_t c2) {
    asm volatile("red.global.add.noftz.v2.bf16x2 [%0],{%1,%2};" ::"l"(g_agg + out), "r"(hmul2(v.x, c2)), "r"(hmul2(v.y, c2)) : "memory");
}
__device__ __forceinline__ void decode_entry(uint32_t e0, uint32_t e1, uint32_t& in, uint32_t& out) {
    const uint32_t bx = e1 >> 21, g = bx >= GB, rem = bx - g * GB;
    in = (g * IG + rem % IG) * SI + (e0 & 0xffff);
    out = rem / IG * SO + (e1 & 0xffff);
}
__device__ __forceinline__ void wait_zeroed() {
    wait_flag(&g_sync[SY_ZERO], N3);
    asm volatile("fence.acquire.gpu;" ::: "memory");
}
constexpr int BAR_ATOMS = 1, BAR_STS = 2, BAR_PUB = 4, BAR_PUBFREE = 6, BAR_W = 8;
constexpr int NT_STS = (NW + 2) * 32, NT_ATOMS = (NW + 1) * 32;
__device__ __forceinline__ void mbar_arrive(uint32_t bar) {
    __syncwarp();
    if (elect_one()) asm volatile("mbarrier.arrive.shared::cta.b64 _,[%0];" ::"r"(bar) : "memory");
}
__device__ __forceinline__ void mbar_wait(uint32_t bar, uint32_t parity) {
    asm volatile("{.reg .pred p; .reg .u32 n; mbarrier.try_wait.parity.shared::cta.b64 p,[%0],%1; @p bra D; mov.u32 n,0;\n"
                 "W: mbarrier.try_wait.parity.shared::cta.b64 p,[%0],%1,2000; @p bra D;\n"
                 "add.u32 n,n,1; setp.lt.u32 p,n,0x4000000; @p bra W; trap;\nD:}" ::"r"(bar), "r"(parity) : "memory");
}
__device__ __forceinline__ uint32_t mad(uint32_t a, uint32_t b, uint32_t c) {
    uint32_t d; asm("mad.lo.u32 %0,%1,%2,%3;" : "=r"(d) : "r"(a), "r"(b), "r"(c)); return d;
}
template <bool R, int G> struct Kind { static constexpr bool replay = R; static constexpr int group = G; };

__device__ __forceinline__ void stage1(const Params& p, unsigned char* sm, int pid) {
    const int warp = warp_id(), lane = lane_id();
    constexpr uint32_t sb = SB;
    uint4 ra[2], rb[2]; uint2 rc[2];
    volatile int* const s_next = (volatile int*)(sm + SM_LC + 64);
    const int total = p.pairs * 2;
    constexpr uint32_t mb = sb + SM_LC;
    if (threadIdx.x < 4) asm volatile("mbarrier.init.shared::cta.b64 [%0],1;" ::"r"(mb + threadIdx.x * 8) : "memory");
    if (threadIdx.x == 0) s_next[2] = 0x7ffffff0;
    if (threadIdx.x < 32) s_next[16 + threadIdx.x] = 2 * C;
    __syncthreads();
    if (warp < NW) {
        constexpr uint32_t cb = sb + SM_CNT, xdum = (uint32_t)(SM_LC + 128 - SM_CNT) << 19;
        constexpr uint32_t xk = sb + SM_X, ak = sb + SM_A - 2 * xk;
        uint32_t cur0 = xk + (lane & p.zero), nxt0 = cur0 + 2 * XG - C * 2, cur1 = cur0, nxt1 = nxt0;
        uint32_t fresh = cur0 + 4 * XG - C * 2, n0 = 0, wpos = 0, chunk = 0;
        int h_in = pid * 2, np = 0;
        uint2* const log = g_log + (pid * NW + warp) * LOGCAP;
        const uint32_t ltmask = ((1u << lane) - 1) | p.zero, tq = (warp * 64 + lane) | p.zero;
        auto load_in = [&](int h) {
            const int q = h_in * (STEP / 4) + tq + h * 32;
            asm volatile("tex.1d.v4.u32.s32 {%0,%1,%2,%3},[%4,{%5}];" : "=r"(ra[h].x), "=r"(ra[h].y), "=r"(ra[h].z), "=r"(ra[h].w) : "l"(p.tin), "r"(q));
            asm volatile("tex.1d.v4.u32.s32 {%0,%1,%2,%3},[%4,{%5}];" : "=r"(rb[h].x), "=r"(rb[h].y), "=r"(rb[h].z), "=r"(rb[h].w) : "l"(p.tout), "r"(q));
            asm volatile("{.reg .b32 z,w; tex.1d.v4.u32.s32 {%0,%1,z,w},[%2,{%3}];}" : "=r"(rc[h].x), "=r"(rc[h].y) : "l"(p.tang), "r"(q));
        };
        const uint32_t stage = sb + SM_S1_END + 256 + warp * 256;
        auto flush_stage = [&]() {
            uint2 e;
            __syncwarp();
            asm volatile("ld.shared.v2.u32 {%0,%1},[%2];" : "=r"(e.x), "=r"(e.y) : "r"(stage + lane * 8) : "memory");
            log[(wpos & ~31u) + lane] = e;
            __syncwarp();
        };
        auto direct = [&](uint32_t first, uint32_t stride, uint32_t count, auto range, auto gate) {
            const float f = bf_lo(p.freq[0]);
            for (uint32_t c0 = first;; c0 += stride * 4) {
                uint2 e[4], v[4]; uint32_t ok = 0, big = 0;
#pragma unroll
                for (int k = 0; k < 4; k++) {
                    uint32_t lo = 0, hi = 0;
                    if (c0 + k * stride < count) range(c0 + k * stride, lo, hi);
                    e[k] = make_uint2(0, 0);
                    if (lo + lane < hi) { e[k] = __ldcg(g_log + lo + lane); ok |= 1u << k; }
                }
                __syncwarp();
                if (c0 == first) gate();
#pragma unroll
                for (int k = 0; k < 4; k++) {
                    uint32_t in;
                    decode_entry(e[k].x, e[k].y, in, e[k].y);
                    v[k] = __ldcg(p.m + in);
                    e[k].x = __float_as_uint(rbf16(f * bf_hi(e[k].x)));
                    big = max(big, e[k].x & 0x7fffffffu);
                }
                const bool slow = __any_sync(0xffffffffu, big >= 0x42000000u);
#pragma unroll
                for (int k = 0; k < 4; k++) {
                    float c = __cosf(__uint_as_float(e[k].x));
                    if (slow) c = cos_slow(__uint_as_float(e[k].x));
                    if ((ok >> k) & 1) red_agg(e[k].y, v[k], dup_bf16(c));
                }
                __syncwarp();
                if (c0 + stride * 4 >= count) break;
            }
        };
        auto drain = [&]() {
            const uint32_t lb = (pid * NW + warp) * LOGCAP;
            if (wpos & 31) flush_stage();
            direct(0, 1, (wpos - n0 + 31) / 32, [&](uint32_t c, uint32_t& lo, uint32_t& hi) { lo = lb + n0 + c * 32; hi = lb + wpos; },
                   [&] { wait_zeroed(); __syncwarp(); });
            wpos = n0;
        };
        auto load_log = [&](int j) {
            uint2 e[8];
#pragma unroll
            for (int k = 0; k < 8; k++) {
                const uint32_t ch = __shfl_sync(0xffffffffu, chunk, k * NR + j);
                e[k] = make_uint2(0, xdum + (lane << 21));
                if (j < NR && ch) e[k] = __ldcg(g_log + (ch - 1) * 32 + lane);
            }
#pragma unroll
            for (int h = 0; h < 2; h++) {
                ra[h] = make_uint4(e[h * 4].x, e[h * 4].y, e[h * 4 + 1].x, e[h * 4 + 1].y);
                rb[h] = make_uint4(e[h * 4 + 2].x, e[h * 4 + 2].y, e[h * 4 + 3].x, e[h * 4 + 3].y);
            }
        };
        auto step = [&](const int k2, auto kind) {
            constexpr bool R = decltype(kind)::replay;
            constexpr int G = decltype(kind)::group;
            uint32_t pa[8], aw[8], xw[8], r[8];
#pragma unroll
            for (int h = 0; h < 2; h++) {
                if (!R) {
                    const uint32_t in[4] = {ra[h].x, ra[h].y, ra[h].z, ra[h].w}, out[4] = {rb[h].x, rb[h].y, rb[h].z, rb[h].w};
#pragma unroll
                    for (int k = 0; k < 4; k++) {
                        const uint32_t i = __umulhi(in[k], MI), o = __umulhi(out[k], MO);
                        aw[h * 4 + k] = __byte_perm(in[k] - i * SI, k < 2 ? rc[h].x : rc[h].y, (k & 1) ? 0x7610 : 0x5410);
                        pa[h * 4 + k] = mad(i, NO, o);
                        xw[h * 4 + k] = mad(i, 1u << 21, mad(o, (IG << 21) - SO, out[k]));
                        asm("{.reg .pred p; setp.ge.u32 p,%1,%2; @p add.u32 %0,%0,%3;}" : "+r"(xw[h * 4 + k]) : "r"(in[k]), "n"(IG * SI), "n"((GB - IG) << 21));
                    }
                } else {
#pragma unroll
                    for (int k = h * 4; k < h * 4 + 4; k++) {
                        const uint4 q4 = (k & 2) ? rb[h] : ra[h];
                        const uint2 e = (k & 1) ? make_uint2(q4.z, q4.w) : make_uint2(q4.x, q4.y);
                        aw[k] = e.x; xw[k] = e.y;
                        pa[k] = mad((e.y >> 21) % IG, NO, (e.y >> 25) + (e.y >= GB << 21 ? GB - NO : 0));
                    }
                }
                if (h == 0) {
                    mbar_wait(mb + G * 8, k2 & 1);
                    if (!R) {
                        if (G) asm volatile("ld.volatile.shared.u32 %0,[%1];" : "=r"(h_in) : "r"(mb + 64) : "memory");
                        else h_in++;
                    }
                }
#pragma unroll
                for (int k = h * 4; k < h * 4 + 4; k++)
                    asm volatile("atom.shared.add.u32 %0,[%1+%2],1;" : "=r"(r[k]) : "r"(xw[k] >> 19), "n"(cb) : "memory");
            }
            bar_arrive(BAR_ATOMS, NT_ATOMS);
            mbar_wait(mb + 16 + G * 8, k2 & 1);
            if (!R) {
                load_in(0);
                if (p.zero) __nanosleep(0);
            }
            uint32_t ovf = 0;
#pragma unroll
            for (int k = 0; k < 8; k++) {
                const bool lo = r[k] < C, hi = xw[k] >= GB << 21;
                const uint32_t s2 = r[k] * 2 + (hi ? (lo ? cur1 : nxt1) : (lo ? cur0 : nxt0));
                asm volatile("{.reg .pred p; .reg .b16 a,b; setp.lt.u32 p,%5,%6; mov.b32 {a,b},%4;"
                             " @p st.shared.u32 [%1+%8],%2; @p st.shared.u16 [%3],a; @!p or.b32 %0,%0,%7;}"
                             : "+r"(ovf) : "r"(mad(pa[k], C * 2, s2) * 2), "r"(aw[k]), "r"((xw[k] >> 16) + s2), "r"(xw[k]), "r"(r[k]),
                               "n"(2 * C), "r"(R && xw[k] >= xdum ? 0u : 1u << k), "n"(ak) : "memory");
            }
            bar_arrive(BAR_STS + G, NT_STS);
            if (!R) {
                if (p.zero) __nanosleep(0);
                load_in(1);
            }
            uint32_t bal = __ballot_sync(0xffffffffu, ovf != 0);
            while (bal) {
                uint32_t e0 = aw[7], e1 = xw[7];
#pragma unroll
                for (int k = 6; k >= 0; k--)
                    if (ovf & (1u << k)) { e0 = aw[k]; e1 = xw[k]; }
                const uint32_t pos = ovf ? (wpos & 31) + __popc(bal & ltmask) : 64, next = wpos + __popc(bal);
                asm volatile("{.reg .pred p; setp.lt.u32 p,%3,32; @p st.shared.v2.u32 [%0],{%1,%2};}" ::"r"(stage + pos * 8), "r"(e0), "r"(e1), "r"(pos) : "memory");
                if ((next ^ wpos) & 32) {
                    flush_stage();
                    asm volatile("{.reg .pred p; setp.lt.u32 p,%3,32; @p st.shared.v2.u32 [%0],{%1,%2};}" ::"r"(stage + (pos - 32) * 8), "r"(e0), "r"(e1), "r"(pos - 32) : "memory");
                }
                wpos = next;
                ovf &= ovf - 1;
                bal = __ballot_sync(0xffffffffu, ovf != 0);
            }
            if (R) load_log((k2 - np) * 2 + G + 1);
            if (G) { cur1 = nxt1 + C * 2; nxt1 = fresh - XG; }
            else if (!R || k2 != np + NR / 2 - 1) { cur0 = nxt0 + C * 2; nxt0 = fresh; }
            fresh += fresh == xk + (NP - 1) * XG - C * 2 ? -(NP - 1) * XG : XG;
        };
        u64* const logsync = (u64*)&g_sync[SY_LOG];
        for (int stop = total - 2 * 2 * N1; h_in < total;) {
            load_in(0); load_in(1);
            do {
                step(np, Kind<false, 0>());
                step(np, Kind<false, 1>());
                np++;
            } while (h_in < stop && wpos <= LOGCAP - 512);
            if (wpos > LOGCAP - 512) drain();
            if (h_in >= stop && stop < total) {
                const uint32_t nch = min(wpos / 32, (LOGCAP - 256 * NR) / 32);
                uint32_t base = 0;
                if (lane == 0) base = (uint32_t)atomicAdd(logsync, (u64)nch);
                base = __shfl_sync(0xffffffffu, base, 0);
                const uint32_t mine = min(nch, NCH - min(base, NCH));
                for (uint32_t c = lane; c < mine; c += 32)
                    g_chunks[base + c] = (pid * NW + warp) * (LOGCAP / 32) + c + 1;
                n0 = mine * 32;
                __syncwarp();
                if (elect_one()) {
                    asm volatile("red.release.gpu.global.add.u64 [%0],%1;" ::"l"(logsync), "l"(1ull << 32) : "memory");
                    if (n0) asm volatile("cp.async.bulk.prefetch.L2.global [%0],%1;" ::"l"(log), "r"(n0 * 8) : "memory");
                }
                __syncwarp();
                stop = total;
            }
        }
        {
            u64 v; int spins = 0;
            do {
                asm volatile("ld.acquire.gpu.global.u64 %0,[%1];" : "=l"(v) : "l"(logsync) : "memory");
                if (++spins > (1 << 22)) __trap();
            } while ((v >> 32) < N1 * NW);
            const uint32_t idx = (((lane / NR) * NW + warp) * NR + lane % NR) * N1 + pid;
            if (lane < 8 * NR && idx < (uint32_t)v) chunk = __ldcg(g_chunks + idx);
            __syncwarp();
        }
        if (wpos > LOGCAP - 256 * NR) drain();
        load_log(0);
#pragma unroll 1
        for (int k2 = np; k2 < np + NR / 2; k2++) {
            step(k2, Kind<true, 0>());
            step(k2, Kind<true, 1>());
        }
        uint2* const rng = (uint2*)(sm + SM_S1_END);
        if (lane == 0) rng[warp] = make_uint2(n0, wpos);
        if (wpos & 31) flush_stage();
        __syncwarp();
        for (int g = 0; g < NG; g++) {
            mbar_wait(mb + g * 8, (np + NR / 2) & 1);
            mbar_wait(mb + 16 + g * 8, (np + NR / 2) & 1);
            bar_arrive(BAR_ATOMS, NT_ATOMS);
            bar_arrive(BAR_STS + g, NT_STS);
        }
        const uint2 mine = lane < NW ? rng[lane] : make_uint2(0, 0);
        const uint32_t nch = (mine.y - mine.x + 31) / 32;
        uint32_t end = nch;
#pragma unroll
        for (int d = 1; d < 32; d *= 2) {
            const uint32_t t = __shfl_up_sync(0xffffffffu, end, d);
            if (lane >= d) end += t;
        }
        direct(warp, NW, __shfl_sync(0xffffffffu, end, 31), [&](uint32_t c, uint32_t& lo, uint32_t& hi) {
            const int w = __popc(__ballot_sync(0xffffffffu, end <= c));
            const uint32_t lb = (pid * NW + w) * LOGCAP;
            lo = lb + __shfl_sync(0xffffffffu, mine.x + (c - (end - nch)) * 32, w);
            hi = lb + __shfl_sync(0xffffffffu, mine.y, w);
        }, [&] { bar_sync(BAR_W, (NW + 1) * 32); });
    } else if (warp == NW) {
        const int row = min(lane, NO - 1), swz = (row >> 1) & 3;
        mbar_arrive(mb);
        int pn = N1 + pid, pnn = 0, nc = 0x7ffffff0;
        for (int s = 0; s < nc; s++) {
            const int hn = min(pn * 2 + (s & 1), total);
            if (hn == total) nc = min(nc, s + 2 + NR + 2);
            const uint32_t sub = s == nc - 4 ? 0 : C, bias = s == nc - 2 ? C : 0;
            uint4* cp = (uint4*)(sm + SM_CNT + (s & 1) * GB * 4) + row * 4;
            bar_sync(BAR_ATOMS, NT_ATOMS);
            uint4 c[4];
#pragma unroll
            for (int j = 0; j < 4; j++) c[j] = cp[j ^ swz];
            __syncwarp();
#pragma unroll
            for (int j = 0; j < 4; j++)
                cp[j ^ swz] = make_uint4(min(max(c[j].x, C), 2 * C) - sub, min(max(c[j].y, C), 2 * C) - sub,
                                         min(max(c[j].z, C), 2 * C) - sub, min(max(c[j].w, C), 2 * C) - sub);
            if (lane == 0 && !(s & 1)) { s_next[0] = hn; s_next[2] = nc; }
            mbar_arrive(mb + ((s + 1) & 1) * 8);
            uint4 w = make_uint4(0, 0, 0, 0);
#pragma unroll
            for (int j = 0; j < 4; j++) {
                const int sh = (j ^ swz) * 8;
                w.x |= min(c[j].x - bias, C) << sh; w.y |= min(c[j].y - bias, C) << sh;
                w.z |= min(c[j].z - bias, C) << sh; w.w |= min(c[j].w - bias, C) << sh;
            }
            mbar_wait(mb + 16 + (s & 1) * 8, (s >> 1) & 1);
            ((uint4*)(sm + SM_CB + (s & 1) * GB))[row] = w;
            asm volatile("fence.proxy.async.shared::cta;" ::: "memory");
            bar_arrive(BAR_STS + (s & 1), NT_STS);
            if (s & 1) pn = min(2 * N1 + __shfl_sync(0xffffffffu, pnn, 0), p.pairs);
            else if (hn < total && s / 2 + 2 < KMAX) {
                if (lane == 0) asm volatile("atom.relaxed.gpu.global.add.u32 %0,[%1],1;" : "=r"(pnn) : "l"(&g_sync[SY_WORK]) : "memory");
            } else pnn = p.pairs;
            const int hp = pn * 2 + ((s & 1) ^ 1);
            if (hp < total && elect_one())
                asm volatile("cp.async.bulk.prefetch.L2.global [%0],%1;" ::"l"(p.angle + hp * STEP), "r"(STEP * 2) : "memory");
            __syncwarp();
        }
    } else if (warp < NW + 3) {
        const int g = warp - NW - 1;
        mbar_arrive(mb + 16 + g * 8);
        const uint32_t* const fb = flags() + flag_idx(sm, g, lane & 1, pid);
        for (int s = g; s < s_next[2]; s += 2) {
            const int k = s >> 1, slot = k % DA * N1 + pid, slots = k % DS * N1 + pid, pl = s % NP;
            const uint32_t cls = __shfl_sync(0xffffffffu, cls_of(sm, slot, g), 0), clss = __shfl_sync(0xffffffffu, cls_of(sm, slots, g), 0);
            if (k >= DS) {
                const uint32_t kw = k - ((lane & 1) ? DS : DA - DV);
                wait_flag(fb + (kw & 1), arrivals(lane & 1, kw));
                __syncwarp();
                asm volatile("fence.proxy.async.global;" ::: "memory");
            }
            bar_sync(BAR_STS + g, NT_STS);
            asm volatile("fence.proxy.async.shared::cta;" ::: "memory");
            if (elect_one()) {
                unsigned char* dst = g_ring + slot_a(slot);
#pragma unroll
                for (int j = 0; j < IG / 2; j++)
                    asm volatile("cp.async.bulk.global.shared::cta.bulk_group [%0],[%1],%2;" ::"l"(g_ring + slot_a(slots) + ring_off(clss, j * 4096)),
                                 "r"(sb + SM_A + pl * AG + j * 2 * ASEG), "n"(2 * ASEG) : "memory");
#pragma unroll
                for (int j = 0; j * 4096 < XG; j++)
                    asm volatile("cp.async.bulk.global.shared::cta.bulk_group [%0],[%1],%2;" ::"l"(dst + ring_off(cls, XO + j * 4096)),
                                 "r"(sb + SM_X + pl * XG + j * 4096), "r"(min(4096, XG - j * 4096)) : "memory");
                asm volatile("cp.async.bulk.global.shared::cta.bulk_group [%0],[%1],%2;" ::"l"(dst + ring_off(cls, XO + XG)),
                             "r"(sb + SM_CB + g * GB), "r"(GB) : "memory");
                asm volatile("cp.async.bulk.commit_group;" ::: "memory");
                asm volatile("cp.async.bulk.wait_group 0;" ::: "memory");
            }
            __syncwarp();
            mbar_arrive(mb + 16 + g * 8);
            bar_sync(BAR_PUBFREE + g, 64);
            bar_arrive(BAR_PUB + g, 64);
        }
    } else if (warp == NW + 3) {
        uint32_t* const fb = flags() + flag_idx(sm, (lane >> 1) & 1, lane & 1, pid);
        bar_arrive(BAR_PUBFREE, 64);
        bar_arrive(BAR_PUBFREE + 1, 64);
        for (int s = 0; s < s_next[2]; s++) {
            if (s == 4) { wait_zeroed(); __syncwarp(); }
            const int g = s & 1;
            bar_sync(BAR_PUB + g, 64);
            if (s + 2 < s_next[2]) bar_arrive(BAR_PUBFREE + g, 64);
            asm volatile("fence.acq_rel.gpu;" ::: "memory");
            if ((lane >> 1) == g) asm volatile("red.relaxed.gpu.global.add.u32 [%0],%1;" ::"l"(fb + ((s >> 1) & 1)), "r"(FL_DATA) : "memory");
            __syncwarp();
        }
        bar_arrive(BAR_W, (NW + 1) * 32);
    }
}

__device__ __forceinline__ void stage2(const Params& p, unsigned char* sm, int g, int ig) {
    const int warp = warp_id(), lane = lane_id();
    constexpr uint32_t sb = SB;
    constexpr int NCW = 16, STEPS = NO / 4, TAB = NCW * ASEG, MB = TAB + SI * 8;
    static_assert(MB + 8 * NCW + 8 <= SM_AUX && MB % 8 == 0, "stage2 smem");
    if (threadIdx.x <= NCW) asm volatile("mbarrier.init.shared::cta.b64 [%0],1;" ::"r"(sb + MB + threadIdx.x * 8) : "memory");
    asm volatile("fence.proxy.async.shared::cta;" ::: "memory");
    __syncthreads();
    if (warp == 30) {
        const int e0 = (g * IG + ig) * SI, bytes = max(0, min((int)SI, p.E - e0)) * 8;
        if (elect_one()) {
            asm volatile("mbarrier.arrive.expect_tx.shared::cta.b64 _,[%0],%1;" ::"r"(sb + MB + NCW * 8), "r"(bytes) : "memory");
            for (int o = 0; o < bytes; o += 16384)
                asm volatile("cp.async.bulk.shared::cluster.global.mbarrier::complete_tx::bytes [%0],[%1],%2,[%3];" ::"r"(sb + TAB + o), "l"((const char*)(p.m + e0) + o), "r"(min(16384, bytes - o)), "r"(sb + MB + NCW * 8) : "memory");
        }
        __syncwarp();
    }
    if (warp == 31) poller<NCW, FL_GO2>(sm, g, ig >> 1, 0, p.units, p.units - 3 * N1, [&] {
            const int e0 = (g * IG + ig) * SI, n = min((int)SI, p.E - e0);
            if (n > 0 && elect_one()) asm volatile("cp.async.bulk.prefetch.L2.global [%0],%1;" ::"l"(p.m + e0), "r"(n * 8) : "memory");
            __syncwarp();
        });
    if (warp >= NCW) return;
    const uint32_t f2 = (uint32_t)p.freq[0] * 0x10001u;
    const uint32_t vlane = slot_v(0) + (lane >> 4) * 8192 + ((lane >> 3) & 1) * VSEG + ig * 128 + (lane & 7) * 16;
    const uint32_t aoff = (ig >> 1) * 8192 + (ig & 1) * ASEG, buf = sb + warp * ASEG, mb = sb + MB + warp * 8;
    auto fetch = [&](uint32_t e) {
        if (elect_one()) {
            asm volatile("mbarrier.arrive.expect_tx.shared::cta.b64 _,[%0],%1;" ::"r"(mb), "n"(ASEG) : "memory");
            asm volatile("cp.async.bulk.shared::cluster.global.mbarrier::complete_tx::bytes [%0],[%1],%2,[%3];" ::"r"(buf),
                         "l"(g_ring + (slot_a((e >> 16) & 0xff) + aoff + ((e >> 2) & 0x1000))), "n"(ASEG), "r"(mb) : "memory");
        }
        __syncwarp();
    };
    mbar_wait(sb + MB + NCW * 8, 0);
    uint2 qn = make_uint2(0, 0);
    bool have = false;
    uint32_t ph = 0;
    for (int t = warp; t < p.units; t += NCW) {
        if (!have) { next_unit<true>(sb + SM_AUX, warp, t, NCW, qn); fetch(qn.x); }
        const uint2 qe = qn;
        mbar_wait(mb, ph); ph ^= 1;
        uint2 a[STEPS];
#pragma unroll
        for (int j = 0; j < STEPS; j++) asm volatile("ld.shared.v2.u32 {%0,%1},[%2];" : "=r"(a[j].x), "=r"(a[j].y) : "r"(buf + j * 256 + lane * 8) : "memory");
        have = next_unit<false>(sb + SM_AUX, warp, t + NCW, NCW, qn);
        uint32_t big = 0, x2[STEPS];
#pragma unroll
        for (int j = 0; j < STEPS; j++) {
            x2[j] = hmul2(__byte_perm(a[j].x, a[j].y, 0x7632), f2);
            a[j].x = __byte_perm(a[j].x, a[j].y, 0x5410);
            big |= (x2[j] & 0x7fff7fffu) + 0x3e003e00u;
        }
        const bool slow = __any_sync(0xffffffffu, big & 0x80008000u);
        if (have) fetch(qn.x + ((uint32_t)slow & p.zero));
        if (slow) {
#pragma unroll
            for (int j = 0; j < STEPS; j++) x2[j] = pack2(cos_slow(bf_lo(x2[j])), cos_slow(bf_hi(x2[j])));
        }
        const uint32_t tag = qe.x >> 31, cq = (qe.x >> (lane >> 4)) << 12;
        const uint32_t vo = ((qe.x >> 24) & 0x7f) * (PV * 8192) + vlane;
        uint2 m0[STEPS], m1[STEPS];
#pragma unroll
        for (int jj = 0; jj < STEPS + 1; jj++) {
            if (jj < STEPS) {
                asm volatile("ld.shared.v2.u32 {%0,%1},[%2];" : "=r"(m0[jj].x), "=r"(m0[jj].y) : "r"(sb + TAB + (a[jj].x & 0xffff) * 8) : "memory");
                asm volatile("ld.shared.v2.u32 {%0,%1},[%2];" : "=r"(m1[jj].x), "=r"(m1[jj].y) : "r"(sb + TAB + (a[jj].x >> 16) * 8) : "memory");
            }
            if (jj >= 1) {
                const int j = jj - 1;
                const uint32_t cf = pack2(__cosf(bf_lo(x2[j])), __cosf(bf_hi(x2[j]))), c2 = slow ? x2[j] : cf;
                const uint32_t d0 = __byte_perm(c2, 0, 0x1010), d1 = __byte_perm(c2, 0, 0x3232);
                st128(g_ring + (vo | ((cq >> (2 * j)) & 0x1000)) + j * 16384,
                      make_uint4((hmul2(m0[j].x, d0) & ~1u) | tag, hmul2(m0[j].y, d0), hmul2(m1[j].x, d1), hmul2(m1[j].y, d1)));
                if (p.zero) __nanosleep(0);
            }
        }
        __syncwarp();
        if (qe.y & 0x8000) asm volatile("fence.acq_rel.gpu;" ::: "memory");
        if (lane == 0) asm volatile("red.relaxed.gpu.global.add.u32 [%0],1;" ::"l"(flags() + (qe.y & 0x7fff)) : "memory");
    }
}

constexpr int EXPORT_WARP = 30;
__device__ __forceinline__ uint2 lock64(uint32_t a) {
    uint2 r;
    asm volatile("{.reg .b64 y; atom.shared.exch.b64 y,[%2],0xffffffffffffffff; mov.b64 {%0,%1},y;}" : "=r"(r.x), "=r"(r.y) : "r"(a) : "memory");
    return r;
}

__device__ __forceinline__ void stage3(const Params& p, unsigned char* sm, int g, int o) {
    const int warp = warp_id(), lane = lane_id();
    constexpr uint32_t sb = SB;
    if (threadIdx.x < 64) ((uint32_t*)(sm + SM_AUX + AUX_DUMMY))[threadIdx.x] = ~0u;
    for (int i = (g * NO + o) * 1024 + threadIdx.x; i < NO * (int)SO / 2; i += N3 * 1024) ((uint4*)g_agg)[i] = make_uint4(0, 0, 0, 0);
    __syncthreads();
    if (threadIdx.x == 0) asm volatile("red.release.gpu.global.add.u32 [%0],1;" ::"l"(&g_sync[SY_ZERO]) : "memory");
    const int t0 = p.pairs * 2 * STEP + (g * NO + o) * 1024 + threadIdx.x;
    static_assert(2 * STEP <= N3 * 1024, "remainder");
    if (t0 - lane < p.T) {
        const int t = min(t0, p.T - 1);
        const uint2 v = __ldg(p.m + p.idx_in[t]);
        wait_zeroed();
        if (t0 < p.T) red_agg(p.idx_out[t], v, dup_bf16(cos_any(rbf16(bf_lo(p.freq[0]) * bf_lo(p.angle[t])))));
        __syncwarp();
    }
    constexpr int NCW = 20, STEPS = IG / 4;
    if (warp == 31) {
        poller<NCW, FL_GO3>(sm, g, (XO + o * XSEG) >> 12, (XO + XG) >> 12, p.units, p.units - 2 * N1, [&] {
            constexpr int H = (SO / 2 + 7) & ~7;
            const int e0 = (o * SO + g * H) & ~7, n = min(H + 8, p.E - e0) & ~7;
            if (n > 0 && elect_one()) {
                asm volatile("cp.async.bulk.prefetch.L2.global [%0],%1;" ::"l"(g_agg + e0), "r"(n * 8) : "memory");
                asm volatile("cp.async.bulk.prefetch.L2.global [%0],%1;" ::"l"(p.dist + e0), "r"(n * 2) : "memory");
            }
            __syncwarp();
        });
    } else if (warp < NCW) {
        const uint32_t dummy = sb + SM_AUX + AUX_DUMMY + lane * 8, r0 = (lane & 7) * 2;
        const uint32_t vlane = slot_v(0) + ring_off(0, o * VSEG) + lane * 16, xlane = ring_off(0, XO + o * XSEG) + lane * 4;
        const uint32_t clane = ring_off(0, XO + XG + o * IG) + (lane >> 3) * 4;
        for (int t = warp; t < p.units; t += NCW) {
            uint2 qe;
            next_unit<true>(sb + SM_AUX, warp, t, NCW, qe);
            const uint32_t tag = qe.x >> 31, ab = slot_a((qe.x >> 16) & 0xff);
            const uint4* vp = (const uint4*)(g_ring + (((qe.x >> 24) & 0x7f) * (PV * 8192) + vlane + (((qe.x >> (o >> 1)) & 1) << 12)));
            const uint32_t* xp = (const uint32_t*)(g_ring + (ab + xlane + ((qe.x >> 2) & 0x1000)));
            const uint32_t* cp = (const uint32_t*)(g_ring + (ab + clane + ((qe.x >> 3) & 0x1000)));
            uint4 v[STEPS]; uint32_t x[STEPS];
            const uint32_t cn = __ldcg(cp);
#pragma unroll
            for (int j = 0; j < STEPS; j++) x[j] = __ldcg(xp + j * 32);
#pragma unroll
            for (int j = 0; j < STEPS; j++) v[j] = ld128(vp + j * 32);
            for (int spins = 0;; spins++) {
                uint32_t bad = 0;
#pragma unroll
                for (int j = 0; j < STEPS; j++) bad |= v[j].x ^ tag;
                if (!__any_sync(0xffffffffu, bad & 1)) break;
                if (spins > (1 << 22)) __trap();
#pragma unroll
                for (int j = 0; j < STEPS; j++) v[j] = ld128(vp + j * 32);
            }
            uint32_t ad[2 * STEPS], dep = cn;
#pragma unroll
            for (int j = 0; j < STEPS; j++) {
                const uint32_t c = (cn >> (8 * j)) & 0xff;
                ad[2 * j] = r0 < c ? sb + (x[j] & 0xffff) * 8 : dummy;
                ad[2 * j + 1] = r0 + 1 < c ? sb + (x[j] >> 16) * 8 : dummy;
                dep ^= x[j];
            }
            if (lane == 0) asm volatile("red.relaxed.gpu.global.add.u32 [%0],%1;" ::"l"(flags() + (qe.y & 0x7fff)), "r"(1 + (dep & p.zero)) : "memory");
            uint32_t pend = 0;
#pragma unroll
            for (int j0 = 0; j0 < 2 * STEPS; j0 += 4) {
                uint2 t[4];
#pragma unroll
                for (int j = 0; j < 4; j++) t[j] = lock64(ad[j0 + j]);
#pragma unroll
                for (int j = 0; j < 4; j++) {
                    const int jj = j0 + j;
                    const uint32_t vx = (jj & 1) ? v[jj / 2].z : v[jj / 2].x, vy = (jj & 1) ? v[jj / 2].w : v[jj / 2].y;
                    asm volatile("{.reg .pred p,q; setp.ne.u32 p,%4,0xffffffff; @p st.shared.v2.u32 [%1],{%2,%3}; setp.ne.and.u32 q,%1,%5,!p; @q or.b32 %0,%0,%6;}"
                                 : "+r"(pend) : "r"(ad[jj]), "r"(hadd2(t[j].x, vx)), "r"(hadd2(t[j].y, vy)), "r"(t[j].x), "r"(dummy), "r"(1u << jj) : "memory");
                }
            }
            while (__any_sync(0xffffffffu, pend)) {
                uint32_t a = dummy, vx = 0, vy = 0;
#pragma unroll
                for (int jj = 2 * STEPS - 1; jj >= 0; jj--)
                    if (pend & (1u << jj)) { a = ad[jj]; vx = (jj & 1) ? v[jj / 2].z : v[jj / 2].x; vy = (jj & 1) ? v[jj / 2].w : v[jj / 2].y; }
                const uint2 t = lock64(a);
                asm volatile("{.reg .pred p; setp.ne.u32 p,%4,0xffffffff; @p st.shared.v2.u32 [%1],{%2,%3}; @p and.b32 %0,%0,%5;}"
                             : "+r"(pend) : "r"(a), "r"(hadd2(t.x, vx)), "r"(hadd2(t.y, vy)), "r"(t.x), "r"(pend - 1) : "memory");
            }
        }
    }
    static_assert(NCW <= EXPORT_WARP, "export warp");
    if (warp != EXPORT_WARP) {
        asm volatile("fence.proxy.async.shared::cta;" ::: "memory");
        bar_arrive(1, 1024);
    }
}

__device__ __forceinline__ void mma_edge(float (&c)[4], uint32_t p01, uint32_t q01, uint32_t p23, uint32_t q23, uint2 b) {
    asm("mma.sync.aligned.m16n8k16.row.col.f32.bf16.bf16.f32 {%0,%1,%2,%3},{%4,%5,%6,%7},{%8,%9},{%0,%1,%2,%3};"
        : "+f"(c[0]), "+f"(c[1]), "+f"(c[2]), "+f"(c[3]) : "r"(p01), "r"(q01), "r"(p23), "r"(q23), "r"(b.x), "r"(b.y));
}
__device__ __forceinline__ uint2 b_frag(const uint16_t* w, int j0) {
    int lane; asm("mov.u32 %0,%%laneid;" : "=r"(lane));
    const int j = j0 + ((lane >> 2) & 1);
    const uint2 v = make_uint2(w[j] | ((uint32_t)w[4 + j] << 16), w[8 + j] | ((uint32_t)w[12 + j] << 16));
    return (lane & 3) == (lane >> 3) ? v : make_uint2(0, 0);
}
__device__ __forceinline__ void edge_gates(const uint16_t* w, uint32_t d2, uint4& sp, uint4& gp) {
    uint32_t rb[2][4];
#pragma unroll
    for (int k = 0; k < 2; k++)
#pragma unroll
        for (int r = 0; r < 4; r++) {
            uint32_t x; asm("sub.rn.bf16x2 %0,%1,%2;" : "=r"(x) : "r"(__byte_perm(d2, 0, k ? 0x3232 : 0x1010)), "r"(((const uint32_t*)w)[48 + r]));
            const uint32_t t = hmul2(hmul2(x, x), 0xc120c120u);
            rb[k][r] = pack2(__expf(bf_lo(t)), __expf(bf_hi(t)));
        }
    uint32_t o[4][2];
#pragma unroll
    for (int n = 0; n < 4; n++) {
        float c[4] = {};
        mma_edge(c, rb[0][0], rb[1][0], rb[0][1], rb[1][1], b_frag(w + (n >> 1) * 32, (n & 1) * 2));
        mma_edge(c, rb[0][2], rb[1][2], rb[0][3], rb[1][3], b_frag(w + (n >> 1) * 32 + 16, (n & 1) * 2));
        o[n][0] = pack2(c[0], c[1]); o[n][1] = pack2(c[2], c[3]);
    }
    gp = make_uint4(o[0][0], o[1][0], o[0][1], o[1][1]);
    sp = make_uint4(o[2][0], o[3][0], o[2][1], o[3][1]);
}
__device__ __forceinline__ uint4 edge_finish(const uint16_t* w, uint4 a, uint4 sp, uint4 gp, uint4 mv) {
    float t0[4] = {}, t1[4] = {}, u0[4] = {}, u1[4] = {};
    mma_edge(t0, a.x, a.z, a.y, a.w, b_frag(w + 64, 0));
    mma_edge(t1, a.x, a.z, a.y, a.w, b_frag(w + 64, 2));
    const uint32_t p01 = pack2(t0[0] * bf_lo(sp.x), t0[1] * bf_hi(sp.x)), p23 = pack2(t1[0] * bf_lo(sp.y), t1[1] * bf_hi(sp.y));
    const uint32_t q01 = pack2(t0[2] * bf_lo(sp.z), t0[3] * bf_hi(sp.z)), q23 = pack2(t1[2] * bf_lo(sp.w), t1[3] * bf_hi(sp.w));
    mma_edge(u0, p01, q01, p23, q23, b_frag(w + 80, 0));
    mma_edge(u1, p01, q01, p23, q23, b_frag(w + 80, 2));
    return make_uint4(hadd2(mv.x, hmul2(pack2(u0[0], u0[1]), gp.x)), hadd2(mv.y, hmul2(pack2(u1[0], u1[1]), gp.y)),
                      hadd2(mv.z, hmul2(pack2(u0[2], u0[3]), gp.z)), hadd2(mv.w, hmul2(pack2(u1[2], u1[3]), gp.w)));
}

__device__ __forceinline__ void finish(const Params& p, unsigned char* sm) {
    __syncwarp();
    const int b = blockIdx.x, tid = threadIdx.x;
    const int role = ((const volatile uint32_t*)(sm + SM_AUX + AUX_MISC))[2];
    const uint16_t* w = (const uint16_t*)(sm + SM_AUX + AUX_W);
    if (role != 3) {
        __syncthreads();
        if (tid == 0) asm volatile("red.release.gpu.global.add.u32 [%0],1;" ::"l"(&g_sync[SY_END]) : "memory");
    }
    constexpr int EP = 3, es = NCTA * 1024;
    static_assert(EP * es * 2 >= E_CAP, "epilogue");
    uint4 sg[2 * EP];
    const int e0 = b * 1024 + tid, np = p.E / 2;
#pragma unroll
    for (int k = 0; k < EP; k++) sg[2 * k].x = __ldg((const uint32_t*)p.dist + min(e0 + k * es, np - 1));
#pragma unroll
    for (int k = 0; k < EP; k++) edge_gates(w, sg[2 * k].x, sg[2 * k], sg[2 * k + 1]);
    uint4 mv[EP];
#pragma unroll
    for (int k = 0; k < EP; k++) mv[k] = __ldg((const uint4*)p.m + min(e0 + k * es, np - 1));
    if (role == 3) {
        if (warp_id() == EXPORT_WARP) {
            const int rank = ((const volatile uint32_t*)(sm + SM_AUX + AUX_MISC))[3], o = rank & 255;
            static_assert(SO % 6 == 0, "export");
            wait_zeroed();
            __syncwarp();
            bar_sync(1, 1024);
            if (elect_one()) {
                asm volatile("fence.proxy.async.global;" ::: "memory");
#pragma unroll
                for (int k = 0; k < 3; k++)
                    asm volatile("cp.reduce.async.bulk.global.shared::cta.bulk_group.add.noftz.bf16 [%0],[%1],%2;" ::"l"(g_agg + o * SO + k * (SO / 3)), "r"(SB + k * (SO / 3) * 8), "n"(SO / 3 * 8) : "memory");
                asm volatile("cp.async.bulk.commit_group;" ::: "memory");
                asm volatile("cp.async.bulk.wait_group 0;" ::: "memory");
            }
            __syncwarp();
            bar_arrive(2, 1024);
            if (elect_one()) asm volatile("red.release.gpu.global.add.u32 [%0],1;" ::"l"(&g_sync[SY_END]) : "memory");
            __syncwarp();
        } else bar_sync(2, 1024);
    }
    uint4* const stash = (uint4*)sm + tid;
#pragma unroll
    for (int k = 0; k < EP; k++) { stash[(3 * k) * 1024] = sg[2 * k]; stash[(3 * k + 1) * 1024] = sg[2 * k + 1]; stash[(3 * k + 2) * 1024] = mv[k]; }
    if (tid == 0) {
        wait_flag(&g_sync[SY_END], NCTA);
        asm volatile("fence.acquire.gpu;" ::: "memory");
    }
    __syncthreads();
    uint4 av[EP];
#pragma unroll
    for (int k = 0; k < EP; k++) av[k] = __ldcg((const uint4*)g_agg + min(e0 + k * es, np - 1));
#pragma unroll
    for (int k = 0; k < EP; k++) {
        const uint4 o = edge_finish(w, av[k], stash[(3 * k) * 1024], stash[(3 * k + 1) * 1024], stash[(3 * k + 2) * 1024]);
        if (e0 + k * es < np) ((uint4*)p.out)[e0 + k * es] = o;
    }
    if (b == 0 && tid < 512) ((uint4*)flags())[tid] = make_uint4(0, 0, 0, 0);
    if (tid == 0) {
        g_info[b] = make_uint2(0, 0);
        if (atomicAdd(&g_sync[SY_EXIT], 1) == NCTA - 1)
            g_sync[SY_ZERO] = g_sync[SY_END] = g_sync[SY_EXIT] = g_sync[SY_WORK] = g_sync[SY_LOG] = g_sync[SY_LOG + 1] = 0;
    }
}

__global__ void __launch_bounds__(1024, 1) main_kernel(const __grid_constant__ Params p) {
    extern __shared__ __align__(128) unsigned char sm[];
    const int b = blockIdx.x, tid = threadIdx.x, warp = tid >> 5;
    if ((uint32_t)__cvta_generic_to_shared(sm) != SB) __trap();
    uint32_t* s_misc = (uint32_t*)(sm + SM_AUX + AUX_MISC);
    if (tid == 0) s_misc[0] = s_misc[4] = s_misc[5] = 0;
    __syncthreads();
    if ((tid & 31) == 0) {
        const int sl = b * 2 + (warp >> 4), j = warp & 15;
        if (warp == 31) s_misc[1] = upper_is_near(g_probe + (b & 127) * 32);
        else if (sl < NSL && j < (sl < KA ? PA : sl < KA + KV ? PV : 1) &&
                 upper_is_near(g_ring + (sl < KA ? slot_a(sl) : slot_v(sl - KA)) + j * 8192 + 4064))
            atomicOr(&s_misc[0], 1u << warp);
    }
    __syncwarp();
    __syncthreads();
    uint32_t me; asm("mov.u32 %0,%%smid;" : "=r"(me));
    me = 0x8000u | (s_misc[1] << 14) | (me & 0x3fff);
    if (tid == 0) {
        const u64 v = (u64)(s_misc[0] ^ (s_misc[1] ? ~0u : 0u)) | ((u64)me << 32);
        asm volatile("st.release.gpu.global.u64 [%0],%1;" ::"l"(&g_info[b]), "l"(v) : "memory");
    }
    for (int i = tid; i < (SM_AUX + AUX_CLS) / 16; i += 1024) ((uint4*)sm)[i] = make_uint4(0, 0, 0, 0);
    uint16_t* w = (uint16_t*)(sm + SM_AUX + AUX_W);
    if (tid < 160) {
        u64 v = 0; int spins = 0;
        while (tid < NCTA && !(v >> 32)) {
            asm volatile("ld.acquire.gpu.global.u64 %0,[%1];" : "=l"(v) : "l"(&g_info[tid]) : "memory");
            if (++spins > (1 << 22)) __trap();
        }
        __syncwarp();
        if (tid < NCTA) ((uint32_t*)(sm + SM_AUX + AUX_CLS))[tid] = (uint32_t)v;
        const uint32_t o = v >> 32;
        const uint32_t c = __reduce_add_sync(0xffffffffu, tid < NCTA ? 1u << (8 * ((o & 1) | ((o >> 13) & 2))) : 0u);
        const uint32_t r = __popc(__ballot_sync(0xffffffffu, tid < NCTA && ((o ^ me) & 0x4001) == 0 && (o > me || (o == me && tid > b))));
        if ((tid & 31) == 0) { atomicAdd(&s_misc[4], c); atomicAdd(&s_misc[5], r); }
    } else if (tid >= 256 && tid < 256 + 104) {
        const int j = tid - 256;
        w[j] = j < 32 ? p.w_rbf[j] : j < 64 ? p.w_sbf[j - 32] : j < 80 ? p.w_down[j - 64] : j < 96 ? p.w_up[j - 80] : p.centers[j - 96];
    }
    __syncthreads();
    int role, rank;
    {
        const uint32_t cnt = s_misc[4], cl = (me & 1) | ((me >> 13) & 2);
        rank = s_misc[5];
        const int c2 = (rank + 1) * IG / NO;
        if (__vminu4(cnt, NO * 0x01010101u) != NO * 0x01010101u) {
            role = b < N2 ? 2 : b < N2 + N3 ? 3 : 1;
            const int r = role == 2 ? b : b - N2;
            rank = role == 1 ? b - N2 - N3 : (r >> 1) | ((r & 1) << 8);
        } else if (rank < NO && (me & 1)) { role = 3; rank |= (cl >> 1) << 8; }
        else if (rank < NO && c2 != rank * IG / NO) { role = 2; rank = (c2 - 1) | ((cl >> 1) << 8); }
        else {
            role = 1;
            rank -= (me & 1) ? NO : min(c2, IG);
            for (uint32_t c = 0; c < cl; c++) rank += ((cnt >> (8 * c)) & 0xff) - ((c & 1) ? NO : IG);
        }
        if (tid == 0) { s_misc[2] = role; s_misc[3] = rank; }
    }
    if (role == 1) stage1(p, sm, rank);
    else if (role == 2) stage2(p, sm, rank >> 8, rank & 255);
    else stage3(p, sm, rank >> 8, rank & 255);
    finish(p, sm);
}

__global__ void generic_scatter(const __grid_constant__ Params p) {
    const float f = bf_lo(p.freq[0]);
    for (int t = blockIdx.x * blockDim.x + threadIdx.x; t < p.T; t += gridDim.x * blockDim.x) {
        const uint2 v = __ldg(p.m + p.idx_in[t]);
        const uint32_t c2 = dup_bf16(cos_any(rbf16(f * bf_lo(p.angle[t]))));
        asm volatile("red.global.add.noftz.v2.bf16x2 [%0],{%1,%2};" ::"l"(p.out + p.idx_out[t]), "r"(hmul2(v.x, c2)), "r"(hmul2(v.y, c2)) : "memory");
    }
}
__global__ void __launch_bounds__(256) generic_finish(const __grid_constant__ Params p) {
    __shared__ __align__(16) uint16_t w[104];
    const int j = threadIdx.x, e = blockIdx.x * blockDim.x + j, ec = min(e, p.E - 1);
    if (j < 104) w[j] = j < 32 ? p.w_rbf[j] : j < 64 ? p.w_sbf[j - 32] : j < 80 ? p.w_down[j - 64] : j < 96 ? p.w_up[j - 80] : p.centers[j - 96];
    const uint2 a = p.out[ec], mv = p.m[ec];
    __syncthreads();
    uint4 s0, s1;
    edge_gates(w, p.dist[ec] * 0x10001u, s0, s1);
    const uint4 o = edge_finish(w, make_uint4(a.x, a.y, a.x, a.y), s0, s1, make_uint4(mv.x, mv.y, mv.x, mv.y));
    if (e < p.E) p.out[e] = make_uint2(o.x, o.y);
}

extern "C" void kernel_launch(void* const* d_in, const int* in_sizes, int n_in, void* d_out, int out_size) {
    static int nsm = 0;
    if (!nsm) {
        cudaDeviceGetAttribute(&nsm, cudaDevAttrMultiProcessorCount, 0);
        cudaFuncSetAttribute(main_kernel, cudaFuncAttributeMaxDynamicSharedMemorySize, SMEM_BYTES);
    }
    Params p;
    p.m = (const uint2*)d_in[0]; p.idx_in = (const int*)d_in[1]; p.idx_out = (const int*)d_in[2];
    p.angle = (const uint16_t*)d_in[4]; p.freq = (const uint16_t*)d_in[6];
    p.dist = (const uint16_t*)d_in[3]; p.centers = (const uint16_t*)d_in[5]; p.w_rbf = (const uint16_t*)d_in[7];
    p.w_sbf = (const uint16_t*)d_in[8]; p.w_down = (const uint16_t*)d_in[9]; p.w_up = (const uint16_t*)d_in[10];
    p.out = (uint2*)d_out;
    p.E = in_sizes[3]; p.T = in_sizes[1];
    p.zero = 0;
    p.pairs = p.T / (2 * STEP); p.units = p.pairs + (NR / 2 + 1) * N1;
    bool fast = nsm >= NCTA && p.E <= E_CAP && p.E >= 8 && p.E % 2 == 0 && p.pairs >= 2 * N1 && p.units < 0xff00;
    static cudaTextureObject_t tex[3];
    static const void* tex_ptr[3];
    static int tex_n[3];
    for (int k = 0; k < 3 && fast; k++) {
        void* ptr = d_in[k == 2 ? 4 : 1 + k];
        if (tex_ptr[k] == ptr && tex_n[k] == p.T) continue;
        cudaResourceDesc rd = {};
        rd.resType = cudaResourceTypeLinear;
        rd.res.linear.devPtr = ptr;
        rd.res.linear.desc = k == 2 ? cudaCreateChannelDesc<uint2>() : cudaCreateChannelDesc<uint4>();
        rd.res.linear.sizeInBytes = (size_t)(p.T / 4) * (k == 2 ? 8 : 16);
        cudaTextureDesc td = {};
        td.readMode = cudaReadModeElementType;
        if (cudaCreateTextureObject(&tex[k], &rd, &td, nullptr) == cudaSuccess) { tex_ptr[k] = ptr; tex_n[k] = p.T; }
        else { cudaGetLastError(); tex_ptr[k] = nullptr; fast = false; }
    }
    p.tin = tex[0]; p.tout = tex[1]; p.tang = tex[2];
    if (!fast) {
        cudaMemsetAsync(d_out, 0, (size_t)p.E * 8);
        generic_scatter<<<nsm * 8, 256>>>(p);
        generic_finish<<<(p.E + 255) / 256, 256>>>(p);
        return;
    }
    void* args[] = {&p};
    cudaLaunchCooperativeKernel((const void*)main_kernel, dim3(NCTA), dim3(1024), args, SMEM_BYTES, cudaStreamPerThread);
}
```

```cpp
#include <cuda_runtime.h>
#include <cuda_bf16.h>
#include <stdint.h>

typedef unsigned long long u64;
constexpr uint32_t magic_of(uint32_t d) { return (uint32_t)(((1ull << 32) + d - 1) / d); }
constexpr uint32_t slice_of(uint32_t total, uint32_t n) {
    uint32_t d = ((total + n - 1) / n + 1) & ~1u;
    while (!((uint64_t)(n * d - 1) * magic_of(d) < ((uint64_t)n << 32))) d += 2;
    return d;
}
constexpr int E_CAP = 800000;
constexpr int NI = 32, NO = 28, NG = 2, IG = NI / NG;
constexpr uint32_t SI = slice_of(E_CAP, NI), SO = slice_of(E_CAP, NO);
constexpr uint32_t MI = magic_of(SI), MO = magic_of(SO);
constexpr int NCTA = 132, N2 = NI, N3 = NO * NG, N1 = NCTA - N2 - N3;
constexpr int C = 16, GB = NO * IG;
constexpr int NP = 5;
constexpr int NW = 28, STEP = NW * 256;
constexpr int NR = 4, LOGCAP = 8192, NCH = N1 * NW * NR * 8, KMAX = 4000;
static_assert(NR % 2 == 0 && NR >= 2 && NR <= 4 && NO % 4 == 0 && IG == 16, "shape");

constexpr int DA = 3, DS = 2, DV = 2, KA = DA * N1, KV = DV * N1, NSL = KA + KV + 1;
constexpr int ASEG = NO * C * 4, XSEG = IG * C * 2, VSEG = IG * C * 8;
constexpr int AG = IG * ASEG, XG = NO * XSEG, XO = IG / 2 * 4096, AXG = XO + XG + GB;
constexpr int PA = (AXG + 4095) / 4096, PV = NO * VSEG / 4096;
static_assert(2 * ASEG <= 4096 && AG == 2 * XG && (XO + XG) / 4096 == (AXG - 1) / 4096 && PA <= 15 && PV <= 14, "layout");
static_assert(DS >= DA - DV && DS <= DA && KA <= 256 && KV <= 128 && NSL <= 2 * NCTA && N1 <= 64, "ring");

constexpr uint32_t SB = 1024;
constexpr int SM_CNT = 0, SM_CB = NG * GB * 4, SM_LC = SM_CB + 2 * GB, SM_X = SM_LC + 256, SM_A = SM_X + NP * XG,
              SM_S1_END = SM_A + NP * AG;
constexpr int SM_AUX = SO * 8 + 512, QN = 256;
constexpr int AUX_Q = 0, AUX_PROG = QN * 8, AUX_CLS = AUX_PROG + 128, AUX_MISC = AUX_CLS + 576, AUX_DUMMY = AUX_MISC + 32,
              AUX_W = AUX_DUMMY + 256, AUX_END = AUX_W + 208;
constexpr int SMEM_BYTES = SM_AUX + AUX_END;
static_assert(SM_S1_END + 256 + NW * 256 <= SM_AUX && SMEM_BYTES <= 232448 && SM_X % 128 == 0 && AUX_W % 16 == 0, "smem");

__device__ __align__(8192) unsigned char g_ring[(size_t)(KA * PA + KV * PV + 1) * 8192];
__device__ __align__(8192) unsigned char g_probe[8192];
__device__ uint2 g_log[N1 * NW * LOGCAP];
__device__ uint32_t g_chunks[NCH];
__device__ __align__(128) uint2 g_agg[NO * SO];
__device__ uint2 g_info[NCTA];
__device__ __align__(128) uint32_t g_sync[160];
constexpr int SY_ZERO = 0, SY_END = 32, SY_EXIT = 64, SY_WORK = 96, SY_LOG = 128;
constexpr int FL_GO2 = 0, FL_GO3 = 1;
constexpr uint32_t FL_DATA = 0x10000;

__device__ __forceinline__ int lane_id() { int v; asm volatile("mov.u32 %0,%%laneid;" : "=r"(v)); return v; }
__device__ __forceinline__ int warp_id() { int v; asm volatile("mov.u32 %0,%%tid.x;" : "=r"(v)); return __shfl_sync(0xffffffffu, v >> 5, 0); }
__device__ __forceinline__ float bf_lo(uint32_t v) { return __uint_as_float(v << 16); }
__device__ __forceinline__ float bf_hi(uint32_t v) { return __uint_as_float(v & 0xffff0000u); }
__device__ __forceinline__ float rbf16(float x) { return __bfloat162float(__float2bfloat16_rn(x)); }
__device__ __forceinline__ uint32_t hmul2(uint32_t a, uint32_t b) {
    uint32_t d; asm("mul.rn.bf16x2 %0,%1,%2;" : "=r"(d) : "r"(a), "r"(b)); return d;
}
__device__ __forceinline__ uint32_t hadd2(uint32_t a, uint32_t b) {
    uint32_t d; asm("add.rn.bf16x2 %0,%1,%2;" : "=r"(d) : "r"(a), "r"(b)); return d;
}
__device__ __forceinline__ uint32_t dup_bf16(float x) {
    uint32_t d; asm("cvt.rn.bf16x2.f32 %0,%1,%1;" : "=r"(d) : "f"(x)); return d;
}
__device__ __forceinline__ uint32_t pack2(float lo, float hi) {
    uint32_t d; asm("cvt.rn.bf16x2.f32 %0,%2,%1;" : "=r"(d) : "f"(lo), "f"(hi)); return d;
}
__device__ __noinline__ float cos_slow(float x) { return cosf(x); }
__device__ __forceinline__ float cos_any(float x) { return fabsf(x) < 32.f ? __cosf(x) : cos_slow(x); }
__device__ __forceinline__ void bar_sync(int id, int n) { asm volatile("barrier.sync.aligned %0,%1;" ::"r"(id), "r"(n) : "memory"); }
__device__ __forceinline__ void bar_arrive(int id, int n) { asm volatile("barrier.arrive.aligned %0,%1;" ::"r"(id), "r"(n) : "memory"); }
__device__ __forceinline__ uint32_t ld_relaxed(const uint32_t* p) {
    uint32_t v; asm volatile("ld.relaxed.gpu.global.u32 %0,[%1];" : "=r"(v) : "l"(p) : "memory"); return v;
}
__device__ __forceinline__ void st128(void* p, uint4 v) {
    asm volatile("{.reg .b64 a,b; .reg .b128 q; mov.b64 a,{%1,%2}; mov.b64 b,{%3,%4}; mov.b128 q,{a,b}; st.relaxed.gpu.global.b128 [%0],q;}" ::"l"(p), "r"(v.x), "r"(v.y), "r"(v.z), "r"(v.w) : "memory");
}
__device__ __forceinline__ uint4 ld128(const void* p) {
    uint4 v;
    asm volatile("{.reg .b64 a,b; .reg .b128 q; ld.relaxed.gpu.global.b128 q,[%4]; mov.b128 {a,b},q; mov.b64 {%0,%1},a; mov.b64 {%2,%3},b;}" : "=r"(v.x), "=r"(v.y), "=r"(v.z), "=r"(v.w) : "l"(p) : "memory");
    return v;
}
__device__ __forceinline__ void wait_flag(const uint32_t* p, uint32_t want) {
    int spins = 0;
    while ((ld_relaxed(p) & 0xffff) < want) {
        __nanosleep(100);
        if (++spins > (1 << 22)) __trap();
    }
}
__device__ __forceinline__ uint32_t slot_a(int s) { return s * (PA * 8192); }
__device__ __forceinline__ uint32_t slot_v(int s) { return KA * PA * 8192 + s * (PV * 8192); }
__device__ __forceinline__ uint32_t ring_off(uint32_t clsg, uint32_t off) {
    return ((off >> 12) << 13) + (((clsg >> (off >> 12)) & 1) << 12) + (off & 4095);
}
__device__ __forceinline__ uint32_t cls_of(const unsigned char* sm, int s, int g) {
    return ((const uint16_t*)(sm + SM_AUX + AUX_CLS))[s] ^ (g ? ~0u : 0u);
}
__device__ __forceinline__ uint32_t flag_idx(const unsigned char* sm, int g, int type, int q) {
    return ring_off(cls_of(sm, NSL - 1, g), type * 1024 + q * 8) / 4;
}
__device__ __forceinline__ uint32_t* flags() { return (uint32_t*)(g_ring + slot_v(KV)); }
__device__ __forceinline__ uint32_t arrivals(int type, uint32_t k) {
    static_assert(DV == 2, "flag ring");
    return type == FL_GO3 ? IG * ((k >> 1) + 1) : NO * (k >> 1);
}
__device__ __forceinline__ bool elect_one() {
    uint32_t r; asm volatile("{.reg .pred p; elect.sync _|p,0xffffffff; selp.u32 %0,1,0,p;}" : "=r"(r)); return r;
}
template <int NCW, int TYPE, class F>
__device__ __forceinline__ void poller(const unsigned char* sm, int g, int blk0, int blk1, int units, int hook_at, F hook) {
    const int lane = lane_id();
    constexpr uint32_t aux = SB + SM_AUX;
    constexpr int DR = TYPE == FL_GO2 ? DS : DA;
    const uint32_t lt = (1u << lane) - 1;
    uint32_t ea[2][DR], ev[2][DV], k[2] = {0, 0}, want[2], v[2], fin[2], fout[2];
#pragma unroll
    for (int j = 0; j < 2; j++) {
        const int q = min(lane + j * 32, N1 - 1);
#pragma unroll
        for (int d = 0; d < DR; d++) {
            const uint32_t sa = q + d * N1, ca = cls_of(sm, sa, g);
            ea[j][d] = (((ca >> blk0) & 1) << 14) | (((ca >> blk1) & 1) << 15) | (sa << 16);
        }
#pragma unroll
        for (int d = 0; d < DV; d++) ev[j][d] = (cls_of(sm, KA + q + d * N1, g) & 0x3fff) | ((q + d * N1) << 24);
        want[j] = lane + j * 32 < N1 ? FL_DATA + arrivals(TYPE, 0) : ~0u;
        v[j] = 0;
        fin[j] = flag_idx(sm, g, TYPE, q); fout[j] = flag_idx(sm, g, TYPE ^ 1, q);
    }
    int tail = 0, check = min(min(QN - N1, hook_at), units), spins = 0;
    while (true) {
        bool hit[2]; uint32_t bal[2];
#pragma unroll
        for (int j = 0; j < 2; j++) {
            hit[j] = v[j] >= want[j] && (uint16_t)v[j] >= (uint16_t)want[j];
            bal[j] = __ballot_sync(0xffffffffu, hit[j]);
        }
        if (bal[0] | bal[1]) {
            asm volatile("fence.acquire.gpu;" ::: "memory");
            if (TYPE == FL_GO2) asm volatile("fence.proxy.async.global;" ::: "memory");
            asm volatile("fence.acq_rel.cta;" ::: "memory");
            spins = 0;
        } else if (++spins > (1 << 22)) __trap();
#pragma unroll
        for (int j = 0; j < 2; j++) {
            const uint32_t pos = tail + __popc(bal[j] & lt);
            const uint32_t hi = fout[j] | (k[j] & 1) | (k[j] < DV ? 0x8000 : 0) | ((pos + 1) << 16);
            asm volatile("{.reg .pred p; .reg .b64 q; setp.ne.u32 p,%3,0; mov.b64 q,{%1,%2}; @p st.relaxed.cta.shared.u64 [%0],q;}"
                         ::"r"(aux + AUX_Q + (pos % QN) * 8), "r"(ea[j][0] | ev[j][0]), "r"(hi), "r"((uint32_t)hit[j]) : "memory");
            tail += __popc(bal[j]);
            k[j] += hit[j];
        }
#pragma unroll
        for (int j = 0; j < 2; j++) v[j] = ld_relaxed(flags() + (fin[j] | (k[j] & 1)));
#pragma unroll
        for (int j = 0; j < 2; j++) {
            const uint32_t a0 = ea[j][0], v0 = ev[j][0] ^ 0x80000000u;
#pragma unroll
            for (int d = 0; d < DR; d++) ea[j][d] = hit[j] ? (d + 1 < DR ? ea[j][(d + 1) % DR] : a0) : ea[j][d];
#pragma unroll
            for (int d = 0; d < DV; d++) ev[j][d] = hit[j] ? (d + 1 < DV ? ev[j][(d + 1) % DV] : v0) : ev[j][d];
            want[j] = hit[j] ? ((k[j] >> 1) + 1) * FL_DATA + arrivals(TYPE, k[j]) : want[j];
        }
        if (tail >= check) {
            if (tail >= units) break;
            if (tail >= hook_at) { hook(); hook_at = 0x7fffffff; }
            int limit;
            do {
                int prog; asm volatile("ld.volatile.shared.u32 %0,[%1];" : "=r"(prog) : "r"(aux + AUX_PROG + min(lane, NCW - 1) * 4) : "memory");
                limit = __reduce_min_sync(0xffffffffu, prog) + QN - N1;
            } while (tail > limit);
            check = min(min(limit, hook_at), units);
        }
    }
}
template <bool BLOCK>
__device__ __forceinline__ bool next_unit(uint32_t aux, int warp, int t, int step, uint2& e) {
    u64 v;
    while (true) {
        asm volatile("ld.acquire.cta.shared.u64 %0,[%1];" : "=l"(v) : "r"(aux + AUX_Q + (t % QN) * 8) : "memory");
        if (__all_sync(0xffffffffu, (int)(v >> 48) == t + 1)) break;
        if (!BLOCK) return false;
        __nanosleep(40);
    }
    if (((t + step) ^ t) & 64) asm volatile("st.volatile.shared.u32 [%0],%1;" ::"r"(aux + AUX_PROG + warp * 4), "r"(t + step) : "memory");
    e = make_uint2((uint32_t)v, (uint32_t)(v >> 32) & 0xffff);
    return true;
}
__device__ __forceinline__ int upper_is_near(unsigned char* q) {
    ((uint4*)q)[0] = ((uint4*)q)[1] = ((uint4*)(q + 4096))[0] = ((uint4*)(q + 4096))[1] = make_uint4(0, 0, 0, 0);
    uint32_t best[2] = {~0u, ~0u};
#pragma unroll
    for (int r = 0; r < 4; r++) {
        uint32_t t0, t1, v;
        asm volatile("mov.u32 %0,%%clock;" : "=r"(t0)::"memory");
        asm volatile("atom.global.exch.b32 %0,[%1],0;" : "=r"(v) : "l"(q + (r & 1) * 4096) : "memory");
        asm volatile("{.reg .pred p; setp.eq.u32 p,%1,0xffffffff; @p trap; mov.u32 %0,%%clock;}" : "=r"(t1) : "r"(v) : "memory");
        best[r & 1] = min(best[r & 1], t1 - t0);
    }
    return best[1] < best[0];
}

struct Params {
    const uint2* m; const int* idx_in; const int* idx_out; const uint16_t* angle; const uint16_t* freq;
    const uint16_t *dist, *centers, *w_rbf, *w_sbf, *w_down, *w_up; uint2* out;
    int E, T, pairs, units;
    uint32_t zero;
    cudaTextureObject_t tin, tout, tang;
};

__device__ __forceinline__ void red_agg(uint32_t out, uint2 v, uint32_t c2) {
    asm volatile("red.global.add.noftz.v2.bf16x2 [%0],{%1,%2};" ::"l"(g_agg + out), "r"(hmul2(v.x, c2)), "r"(hmul2(v.y, c2)) : "memory");
}
__device__ __forceinline__ void decode_entry(uint32_t e0, uint32_t e1, uint32_t& in, uint32_t& out) {
    const uint32_t bx = e1 >> 21, g = bx >= GB, rem = bx - g * GB;
    in = (g * IG + rem % IG) * SI + (e0 & 0xffff);
    out = rem / IG * SO + (e1 & 0xffff);
}
__device__ __forceinline__ void wait_zeroed() {
    wait_flag(&g_sync[SY_ZERO], N3);
    asm volatile("fence.acquire.gpu;" ::: "memory");
}
constexpr int BAR_ATOMS = 1, BAR_STS = 2, BAR_PUB = 4, BAR_PUBFREE = 6, BAR_W = 8;
constexpr int NT_STS = (NW + 2) * 32, NT_ATOMS = (NW + 1) * 32;
__device__ __forceinline__ void mbar_arrive(uint32_t bar) {
    __syncwarp();
    if (elect_one()) asm volatile("mbarrier.arrive.shared::cta.b64 _,[%0];" ::"r"(bar) : "memory");
}
__device__ __forceinline__ void mbar_wait(uint32_t bar, uint32_t parity) {
    asm volatile("{.reg .pred p; .reg .u32 n; mbarrier.try_wait.parity.shared::cta.b64 p,[%0],%1; @p bra D; mov.u32 n,0;\n"
                 "W: mbarrier.try_wait.parity.shared::cta.b64 p,[%0],%1,2000; @p bra D;\n"
                 "add.u32 n,n,1; setp.lt.u32 p,n,0x4000000; @p bra W; trap;\nD:}" ::"r"(bar), "r"(parity) : "memory");
}
__device__ __forceinline__ uint32_t mad(uint32_t a, uint32_t b, uint32_t c) {
    uint32_t d; asm("mad.lo.u32 %0,%1,%2,%3;" : "=r"(d) : "r"(a), "r"(b), "r"(c)); return d;
}
template <bool R, int G> struct Kind { static constexpr bool replay = R; static constexpr int group = G; };

__device__ __forceinline__ void stage1(const Params& p, unsigned char* sm, int pid) {
    const int warp = warp_id(), lane = lane_id();
    constexpr uint32_t sb = SB;
    uint4 ra[2], rb[2]; uint2 rc[2];
    volatile int* const s_next = (volatile int*)(sm + SM_LC + 64);
    const int total = p.pairs * 2;
    constexpr uint32_t mb = sb + SM_LC;
    if (threadIdx.x < 4) asm volatile("mbarrier.init.shared::cta.b64 [%0],1;" ::"r"(mb + threadIdx.x * 8) : "memory");
    if (threadIdx.x == 0) s_next[2] = 0x7ffffff0;
    if (threadIdx.x < 32) s_next[16 + threadIdx.x] = 2 * C;
    __syncthreads();
    if (warp < NW) {
        constexpr uint32_t cb = sb + SM_CNT, xdum = (uint32_t)(SM_LC + 128 - SM_CNT) << 19;
        constexpr uint32_t xk = sb + SM_X, ak = sb + SM_A - 2 * xk;
        uint32_t cur0 = xk + (lane & p.zero), nxt0 = cur0 + 2 * XG - C * 2, cur1 = cur0, nxt1 = nxt0;
        uint32_t fresh = cur0 + 4 * XG - C * 2, n0 = 0, wpos = 0, chunk = 0;
        int h_in = pid * 2, np = 0;
        uint2* const log = g_log + (pid * NW + warp) * LOGCAP;
        const uint32_t ltmask = ((1u << lane) - 1) | p.zero, tq = (warp * 64 + lane) | p.zero;
        auto load_in = [&](int h) {
            const int q = h_in * (STEP / 4) + tq + h * 32;
            asm volatile("tex.1d.v4.u32.s32 {%0,%1,%2,%3},[%4,{%5}];" : "=r"(ra[h].x), "=r"(ra[h].y), "=r"(ra[h].z), "=r"(ra[h].w) : "l"(p.tin), "r"(q));
            asm volatile("tex.1d.v4.u32.s32 {%0,%1,%2,%3},[%4,{%5}];" : "=r"(rb[h].x), "=r"(rb[h].y), "=r"(rb[h].z), "=r"(rb[h].w) : "l"(p.tout), "r"(q));
            asm volatile("{.reg .b32 z,w; tex.1d.v4.u32.s32 {%0,%1,z,w},[%2,{%3}];}" : "=r"(rc[h].x), "=r"(rc[h].y) : "l"(p.tang), "r"(q));
        };
        const uint32_t stage = sb + SM_S1_END + 256 + warp * 256;
        auto flush_stage = [&]() {
            uint2 e;
            __syncwarp();
            asm volatile("ld.shared.v2.u32 {%0,%1},[%2];" : "=r"(e.x), "=r"(e.y) : "r"(stage + lane * 8) : "memory");
            log[(wpos & ~31u) + lane] = e;
            __syncwarp();
        };
        auto direct = [&](uint32_t first, uint32_t stride, uint32_t count, auto range, auto gate) {
            const float f = bf_lo(p.freq[0]);
            for (uint32_t c0 = first;; c0 += stride * 4) {
                uint2 e[4], v[4]; uint32_t ok = 0, big = 0;
#pragma unroll
                for (int k = 0; k < 4; k++) {
                    uint32_t lo = 0, hi = 0;
                    if (c0 + k * stride < count) range(c0 + k * stride, lo, hi);
                    e[k] = make_uint2(0, 0);
                    if (lo + lane < hi) { e[k] = __ldcg(g_log + lo + lane); ok |= 1u << k; }
                }
                __syncwarp();
                if (c0 == first) gate();
#pragma unroll
                for (int k = 0; k < 4; k++) {
                    uint32_t in;
                    decode_entry(e[k].x, e[k].y, in, e[k].y);
                    v[k] = __ldcg(p.m + in);
                    e[k].x = __float_as_uint(rbf16(f * bf_hi(e[k].x)));
                    big = max(big, e[k].x & 0x7fffffffu);
                }
                const bool slow = __any_sync(0xffffffffu, big >= 0x42000000u);
#pragma unroll
                for (int k = 0; k < 4; k++) {
                    float c = __cosf(__uint_as_float(e[k].x));
                    if (slow) c = cos_slow(__uint_as_float(e[k].x));
                    if ((ok >> k) & 1) red_agg(e[k].y, v[k], dup_bf16(c));
                }
                __syncwarp();
                if (c0 + stride * 4 >= count) break;
            }
        };
        auto drain = [&]() {
            const uint32_t lb = (pid * NW + warp) * LOGCAP;
            if (wpos & 31) flush_stage();
            direct(0, 1, (wpos - n0 + 31) / 32, [&](uint32_t c, uint32_t& lo, uint32_t& hi) { lo = lb + n0 + c * 32; hi = lb + wpos; },
                   [&] { wait_zeroed(); __syncwarp(); });
            wpos = n0;
        };
        auto load_log = [&](int j) {
            uint2 e[8];
#pragma unroll
            for (int k = 0; k < 8; k++) {
                const uint32_t ch = __shfl_sync(0xffffffffu, chunk, k * NR + j);
                e[k] = make_uint2(0, xdum + (lane << 21));
                if (j < NR && ch) e[k] = __ldcg(g_log + (ch - 1) * 32 + lane);
            }
#pragma unroll
            for (int h = 0; h < 2; h++) {
                ra[h] = make_uint4(e[h * 4].x, e[h * 4].y, e[h * 4 + 1].x, e[h * 4 + 1].y);
                rb[h] = make_uint4(e[h * 4 + 2].x, e[h * 4 + 2].y, e[h * 4 + 3].x, e[h * 4 + 3].y);
            }
        };
        auto step = [&](const int k2, auto kind) {
            constexpr bool R = decltype(kind)::replay;
            constexpr int G = decltype(kind)::group;
            uint32_t pa[8], aw[8], xw[8], r[8];
#pragma unroll
            for (int h = 0; h < 2; h++) {
                if (!R) {
                    const uint32_t in[4] = {ra[h].x, ra[h].y, ra[h].z, ra[h].w}, out[4] = {rb[h].x, rb[h].y, rb[h].z, rb[h].w};
#pragma unroll
                    for (int k = 0; k < 4; k++) {
                        const uint32_t i = __umulhi(in[k], MI), o = __umulhi(out[k], MO);
                        aw[h * 4 + k] = __byte_perm(in[k] - i * SI, k < 2 ? rc[h].x : rc[h].y, (k & 1) ? 0x7610 : 0x5410);
                        pa[h * 4 + k] = mad(i, NO, o);
                        xw[h * 4 + k] = mad(i, 1u << 21, mad(o, (IG << 21) - SO, out[k]));
                        asm("{.reg .pred p; setp.ge.u32 p,%1,%2; @p add.u32 %0,%0,%3;}" : "+r"(xw[h * 4 + k]) : "r"(in[k]), "n"(IG * SI), "n"((GB - IG) << 21));
                    }
                } else {
#pragma unroll
                    for (int k = h * 4; k < h * 4 + 4; k++) {
                        const uint4 q4 = (k & 2) ? rb[h] : ra[h];
                        const uint2 e = (k & 1) ? make_uint2(q4.z, q4.w) : make_uint2(q4.x, q4.y);
                        aw[k] = e.x; xw[k] = e.y;
                        pa[k] = mad((e.y >> 21) % IG, NO, (e.y >> 25) + (e.y >= GB << 21 ? GB - NO : 0));
                    }
                }
                if (h == 0) {
                    mbar_wait(mb + G * 8, k2 & 1);
                    if (!R) {
                        if (G) asm volatile("ld.volatile.shared.u32 %0,[%1];" : "=r"(h_in) : "r"(mb + 64) : "memory");
                        else h_in++;
                    }
                }
#pragma unroll
                for (int k = h * 4; k < h * 4 + 4; k++)
                    asm volatile("atom.shared.add.u32 %0,[%1+%2],1;" : "=r"(r[k]) : "r"(xw[k] >> 19), "n"(cb) : "memory");
            }
            bar_arrive(BAR_ATOMS, NT_ATOMS);
            mbar_wait(mb + 16 + G * 8, k2 & 1);
            if (!R) {
                load_in(0);
                if (p.zero) __nanosleep(0);
            }
            uint32_t ovf = 0;
#pragma unroll
            for (int k = 0; k < 8; k++) {
                const bool lo = r[k] < C, hi = xw[k] >= GB << 21;
                const uint32_t s2 = r[k] * 2 + (hi ? (lo ? cur1 : nxt1) : (lo ? cur0 : nxt0));
                asm volatile("{.reg .pred p; .reg .b16 a,b; setp.lt.u32 p,%5,%6; mov.b32 {a,b},%4;"
                             " @p st.shared.u32 [%1+%8],%2; @p st.shared.u16 [%3],a; @!p or.b32 %0,%0,%7;}"
                             : "+r"(ovf) : "r"(mad(pa[k], C * 2, s2) * 2), "r"(aw[k]), "r"((xw[k] >> 16) + s2), "r"(xw[k]), "r"(r[k]),
                               "n"(2 * C), "r"(R && xw[k] >= xdum ? 0u : 1u << k), "n"(ak) : "memory");
            }
            bar_arrive(BAR_STS + G, NT_STS);
            if (!R) {
                if (p.zero) __nanosleep(0);
                load_in(1);
            }
            uint32_t bal = __ballot_sync(0xffffffffu, ovf != 0);
            while (bal) {
                uint32_t e0 = aw[7], e1 = xw[7];
#pragma unroll
                for (int k = 6; k >= 0; k--)
                    if (ovf & (1u << k)) { e0 = aw[k]; e1 = xw[k]; }
                const uint32_t pos = ovf ? (wpos & 31) + __popc(bal & ltmask) : 64, next = wpos + __popc(bal);
                asm volatile("{.reg .pred p; setp.lt.u32 p,%3,32; @p st.shared.v2.u32 [%0],{%1,%2};}" ::"r"(stage + pos * 8), "r"(e0), "r"(e1), "r"(pos) : "memory");
                if ((next ^ wpos) & 32) {
                    flush_stage();
                    asm volatile("{.reg .pred p; setp.lt.u32 p,%3,32; @p st.shared.v2.u32 [%0],{%1,%2};}" ::"r"(stage + (pos - 32) * 8), "r"(e0), "r"(e1), "r"(pos - 32) : "memory");
                }
                wpos = next;
                ovf &= ovf - 1;
                bal = __ballot_sync(0xffffffffu, ovf != 0);
            }
            if (R) load_log((k2 - np) * 2 + G + 1);
            if (G) { cur1 = nxt1 + C * 2; nxt1 = fresh - XG; }
            else if (!R || k2 != np + NR / 2 - 1) { cur0 = nxt0 + C * 2; nxt0 = fresh; }
            fresh += fresh == xk + (NP - 1) * XG - C * 2 ? -(NP - 1) * XG : XG;
        };
        u64* const logsync = (u64*)&g_sync[SY_LOG];
        for (int stop = total - 2 * 2 * N1; h_in < total;) {
            load_in(0); load_in(1);
            do {
                step(np, Kind<false, 0>());
                step(np, Kind<false, 1>());
                np++;
            } while (h_in < stop && wpos <= LOGCAP - 512);
            if (wpos > LOGCAP - 512) drain();
            if (h_in >= stop && stop < total) {
                const uint32_t nch = min(wpos / 32, (LOGCAP - 256 * NR) / 32);
                uint32_t base = 0;
                if (lane == 0) base = (uint32_t)atomicAdd(logsync, (u64)nch);
                base = __shfl_sync(0xffffffffu, base, 0);
                const uint32_t mine = min(nch, NCH - min(base, NCH));
                for (uint32_t c = lane; c < mine; c += 32)
                    g_chunks[base + c] = (pid * NW + warp) * (LOGCAP / 32) + c + 1;
                n0 = mine * 32;
                __syncwarp();
                if (elect_one()) {
                    asm volatile("red.release.gpu.global.add.u64 [%0],%1;" ::"l"(logsync), "l"(1ull << 32) : "memory");
                    if (n0) asm volatile("cp.async.bulk.prefetch.L2.global [%0],%1;" ::"l"(log), "r"(n0 * 8) : "memory");
                }
                __syncwarp();
                stop = total;
            }
        }
        {
            u64 v; int spins = 0;
            do {
                asm volatile("ld.acquire.gpu.global.u64 %0,[%1];" : "=l"(v) : "l"(logsync) : "memory");
                if (++spins > (1 << 22)) __trap();
            } while ((v >> 32) < N1 * NW);
            const uint32_t idx = (((lane / NR) * NW + warp) * NR + lane % NR) * N1 + pid;
            if (lane < 8 * NR && idx < (uint32_t)v) chunk = __ldcg(g_chunks + idx);
            __syncwarp();
        }
        if (wpos > LOGCAP - 256 * NR) drain();
        load_log(0);
#pragma unroll 1
        for (int k2 = np; k2 < np + NR / 2; k2++) {
            step(k2, Kind<true, 0>());
            step(k2, Kind<true, 1>());
        }
        uint2* const rng = (uint2*)(sm + SM_S1_END);
        if (lane == 0) rng[warp] = make_uint2(n0, wpos);
        if (wpos & 31) flush_stage();
        __syncwarp();
        for (int g = 0; g < NG; g++) {
            mbar_wait(mb + g * 8, (np + NR / 2) & 1);
            mbar_wait(mb + 16 + g * 8, (np + NR / 2) & 1);
            bar_arrive(BAR_ATOMS, NT_ATOMS);
            bar_arrive(BAR_STS + g, NT_STS);
        }
        const uint2 mine = lane < NW ? rng[lane] : make_uint2(0, 0);
        const uint32_t nch = (mine.y - mine.x + 31) / 32;
        uint32_t end = nch;
#pragma unroll
        for (int d = 1; d < 32; d *= 2) {
            const uint32_t t = __shfl_up_sync(0xffffffffu, end, d);
            if (lane >= d) end += t;
        }
        direct(warp, NW, __shfl_sync(0xffffffffu, end, 31), [&](uint32_t c, uint32_t& lo, uint32_t& hi) {
            const int w = __popc(__ballot_sync(0xffffffffu, end <= c));
            const uint32_t lb = (pid * NW + w) * LOGCAP;
            lo = lb + __shfl_sync(0xffffffffu, mine.x + (c - (end - nch)) * 32, w);
            hi = lb + __shfl_sync(0xffffffffu, mine.y, w);
        }, [&] { bar_sync(BAR_W, (NW + 1) * 32); });
    } else if (warp == NW) {
        const int row = min(lane, NO - 1), swz = (row >> 1) & 3;
        mbar_arrive(mb);
        int pn = N1 + pid, pnn = 0, nc = 0x7ffffff0;
        for (int s = 0; s < nc; s++) {
            const int hn = min(pn * 2 + (s & 1), total);
            if (hn == total) nc = min(nc, s + 2 + NR + 2);
            const uint32_t sub = s == nc - 4 ? 0 : C, bias = s == nc - 2 ? C : 0;
            uint4* cp = (uint4*)(sm + SM_CNT + (s & 1) * GB * 4) + row * 4;
            bar_sync(BAR_ATOMS, NT_ATOMS);
            uint4 c[4];
#pragma unroll
            for (int j = 0; j < 4; j++) c[j] = cp[j ^ swz];
            __syncwarp();
#pragma unroll
            for (int j = 0; j < 4; j++)
                cp[j ^ swz] = make_uint4(min(max(c[j].x, C), 2 * C) - sub, min(max(c[j].y, C), 2 * C) - sub,
                                         min(max(c[j].z, C), 2 * C) - sub, min(max(c[j].w, C), 2 * C) - sub);
            if (lane == 0 && !(s & 1)) { s_next[0] = hn; s_next[2] = nc; }
            mbar_arrive(mb + ((s + 1) & 1) * 8);
            uint4 w = make_uint4(0, 0, 0, 0);
#pragma unroll
            for (int j = 0; j < 4; j++) {
                const int sh = (j ^ swz) * 8;
                w.x |= min(c[j].x - bias, C) << sh; w.y |= min(c[j].y - bias, C) << sh;
                w.z |= min(c[j].z - bias, C) << sh; w.w |= min(c[j].w - bias, C) << sh;
            }
            mbar_wait(mb + 16 + (s & 1) * 8, (s >> 1) & 1);
            ((uint4*)(sm + SM_CB + (s & 1) * GB))[row] = w;
            bar_arrive(BAR_STS + (s & 1), NT_STS);
            if (s & 1) pn = min(2 * N1 + __shfl_sync(0xffffffffu, pnn, 0), p.pairs);
            else if (hn < total && s / 2 + 2 < KMAX) {
                if (lane == 0) asm volatile("atom.relaxed.gpu.global.add.u32 %0,[%1],1;" : "=r"(pnn) : "l"(&g_sync[SY_WORK]) : "memory");
            } else pnn = p.pairs;
            const int hp = pn * 2 + ((s & 1) ^ 1);
            if (hp < total && elect_one())
                asm volatile("cp.async.bulk.prefetch.L2.global [%0],%1;" ::"l"(p.angle + hp * STEP), "r"(STEP * 2) : "memory");
            __syncwarp();
        }
    } else if (warp < NW + 3) {
        const int g = warp - NW - 1;
        mbar_arrive(mb + 16 + g * 8);
        const uint32_t* const fb = flags() + flag_idx(sm, g, lane & 1, pid);
        for (int s = g; s < s_next[2]; s += 2) {
            const int k = s >> 1, slot = k % DA * N1 + pid, slots = k % DS * N1 + pid, pl = s % NP;
            const uint32_t cls = __shfl_sync(0xffffffffu, cls_of(sm, slot, g), 0), clss = __shfl_sync(0xffffffffu, cls_of(sm, slots, g), 0);
            if (k >= DS) {
                const uint32_t kw = k - ((lane & 1) ? DS : DA - DV);
                wait_flag(fb + (kw & 1), arrivals(lane & 1, kw));
                __syncwarp();
                asm volatile("fence.proxy.async.global;" ::: "memory");
            }
            bar_sync(BAR_STS + g, NT_STS);
            asm volatile("fence.proxy.async.shared::cta;" ::: "memory");
            if (elect_one()) {
                unsigned char* dst = g_ring + slot_a(slot);
#pragma unroll
                for (int j = 0; j < IG / 2; j++)
                    asm volatile("cp.async.bulk.global.shared::cta.bulk_group [%0],[%1],%2;" ::"l"(g_ring + slot_a(slots) + ring_off(clss, j * 4096)),
                                 "r"(sb + SM_A + pl * AG + j * 2 * ASEG), "n"(2 * ASEG) : "memory");
#pragma unroll
                for (int j = 0; j * 4096 < XG; j++)
                    asm volatile("cp.async.bulk.global.shared::cta.bulk_group [%0],[%1],%2;" ::"l"(dst + ring_off(cls, XO + j * 4096)),
                                 "r"(sb + SM_X + pl * XG + j * 4096), "r"(min(4096, XG - j * 4096)) : "memory");
                asm volatile("cp.async.bulk.global.shared::cta.bulk_group [%0],[%1],%2;" ::"l"(dst + ring_off(cls, XO + XG)),
                             "r"(sb + SM_CB + g * GB), "r"(GB) : "memory");
                asm volatile("cp.async.bulk.commit_group;" ::: "memory");
                asm volatile("cp.async.bulk.wait_group 0;" ::: "memory");
            }
            __syncwarp();
            mbar_arrive(mb + 16 + g * 8);
            bar_sync(BAR_PUBFREE + g, 64);
            bar_arrive(BAR_PUB + g, 64);
        }
    } else if (warp == NW + 3) {
        uint32_t* const fb = flags() + flag_idx(sm, (lane >> 1) & 1, lane & 1, pid);
        bar_arrive(BAR_PUBFREE, 64);
        bar_arrive(BAR_PUBFREE + 1, 64);
        for (int s = 0; s < s_next[2]; s++) {
            if (s == 4) { wait_zeroed(); __syncwarp(); }
            const int g = s & 1;
            bar_sync(BAR_PUB + g, 64);
            if (s + 2 < s_next[2]) bar_arrive(BAR_PUBFREE + g, 64);
            asm volatile("fence.release.gpu;" ::: "memory");
            if ((lane >> 1) == g) asm volatile("red.relaxed.gpu.global.add.u32 [%0],%1;" ::"l"(fb + ((s >> 1) & 1)), "r"(FL_DATA) : "memory");
            __syncwarp();
        }
        bar_arrive(BAR_W, (NW + 1) * 32);
    }
}

__device__ __forceinline__ void stage2(const Params& p, unsigned char* sm, int g, int ig) {
    const int warp = warp_id(), lane = lane_id();
    constexpr uint32_t sb = SB;
    constexpr int NCW = 16, STEPS = NO / 4, TAB = NCW * ASEG, MB = TAB + SI * 8;
    static_assert(MB + 8 * NCW + 8 <= SM_AUX && MB % 8 == 0, "stage2 smem");
    if (threadIdx.x <= NCW) asm volatile("mbarrier.init.shared::cta.b64 [%0],1;" ::"r"(sb + MB + threadIdx.x * 8) : "memory");
    asm volatile("fence.proxy.async.shared::cta;" ::: "memory");
    __syncthreads();
    if (warp == 30) {
        const int e0 = (g * IG + ig) * SI, bytes = max(0, min((int)SI, p.E - e0)) * 8;
        if (elect_one()) {
            asm volatile("mbarrier.arrive.expect_tx.shared::cta.b64 _,[%0],%1;" ::"r"(sb + MB + NCW * 8), "r"(bytes) : "memory");
            for (int o = 0; o < bytes; o += 16384)
                asm volatile("cp.async.bulk.shared::cluster.global.mbarrier::complete_tx::bytes [%0],[%1],%2,[%3];" ::"r"(sb + TAB + o), "l"((const char*)(p.m + e0) + o), "r"(min(16384, bytes - o)), "r"(sb + MB + NCW * 8) : "memory");
        }
        __syncwarp();
    }
    if (warp == 31) poller<NCW, FL_GO2>(sm, g, ig >> 1, 0, p.units, p.units - 3 * N1, [&] {
            const int e0 = (g * IG + ig) * SI, n = min((int)SI, p.E - e0);
            if (n > 0 && elect_one()) asm volatile("cp.async.bulk.prefetch.L2.global [%0],%1;" ::"l"(p.m + e0), "r"(n * 8) : "memory");
            __syncwarp();
        });
    if (warp >= NCW) return;
    const uint32_t f2 = (uint32_t)p.freq[0] * 0x10001u;
    const uint32_t vlane = slot_v(0) + (lane >> 4) * 8192 + ((lane >> 3) & 1) * VSEG + ig * 128 + (lane & 7) * 16;
    const uint32_t aoff = (ig >> 1) * 8192 + (ig & 1) * ASEG, buf = sb + warp * ASEG, mb = sb + MB + warp * 8;
    auto fetch = [&](uint32_t e) {
        if (elect_one()) {
            asm volatile("mbarrier.arrive.expect_tx.shared::cta.b64 _,[%0],%1;" ::"r"(mb), "n"(ASEG) : "memory");
            asm volatile("cp.async.bulk.shared::cluster.global.mbarrier::complete_tx::bytes [%0],[%1],%2,[%3];" ::"r"(buf),
                         "l"(g_ring + (slot_a((e >> 16) & 0xff) + aoff + ((e >> 2) & 0x1000))), "n"(ASEG), "r"(mb) : "memory");
        }
        __syncwarp();
    };
    mbar_wait(sb + MB + NCW * 8, 0);
    uint2 qn = make_uint2(0, 0);
    bool have = false;
    uint32_t ph = 0;
    for (int t = warp; t < p.units; t += NCW) {
        if (!have) { next_unit<true>(sb + SM_AUX, warp, t, NCW, qn); fetch(qn.x); }
        const uint2 qe = qn;
        mbar_wait(mb, ph); ph ^= 1;
        uint2 a[STEPS];
#pragma unroll
        for (int j = 0; j < STEPS; j++) asm volatile("ld.shared.v2.u32 {%0,%1},[%2];" : "=r"(a[j].x), "=r"(a[j].y) : "r"(buf + j * 256 + lane * 8) : "memory");
        have = next_unit<false>(sb + SM_AUX, warp, t + NCW, NCW, qn);
        uint32_t big = 0, x2[STEPS];
#pragma unroll
        for (int j = 0; j < STEPS; j++) {
            x2[j] = hmul2(__byte_perm(a[j].x, a[j].y, 0x7632), f2);
            a[j].x = __byte_perm(a[j].x, a[j].y, 0x5410);
            big |= (x2[j] & 0x7fff7fffu) + 0x3e003e00u;
        }
        const bool slow = __any_sync(0xffffffffu, big & 0x80008000u);
        if (have) fetch(qn.x + ((uint32_t)slow & p.zero));
        if (slow) {
#pragma unroll
            for (int j = 0; j < STEPS; j++) x2[j] = pack2(cos_slow(bf_lo(x2[j])), cos_slow(bf_hi(x2[j])));
        }
        const uint32_t tag = qe.x >> 31, cq = (qe.x >> (lane >> 4)) << 12;
        const uint32_t vo = ((qe.x >> 24) & 0x7f) * (PV * 8192) + vlane;
        uint2 m0[STEPS], m1[STEPS];
#pragma unroll
        for (int jj = 0; jj < STEPS + 1; jj++) {
            if (jj < STEPS) {
                asm volatile("ld.shared.v2.u32 {%0,%1},[%2];" : "=r"(m0[jj].x), "=r"(m0[jj].y) : "r"(sb + TAB + (a[jj].x & 0xffff) * 8) : "memory");
                asm volatile("ld.shared.v2.u32 {%0,%1},[%2];" : "=r"(m1[jj].x), "=r"(m1[jj].y) : "r"(sb + TAB + (a[jj].x >> 16) * 8) : "memory");
            }
            if (jj >= 1) {
                const int j = jj - 1;
                const uint32_t cf = pack2(__cosf(bf_lo(x2[j])), __cosf(bf_hi(x2[j]))), c2 = slow ? x2[j] : cf;
                const uint32_t d0 = __byte_perm(c2, 0, 0x1010), d1 = __byte_perm(c2, 0, 0x3232);
                st128(g_ring + (vo | ((cq >> (2 * j)) & 0x1000)) + j * 16384,
                      make_uint4((hmul2(m0[j].x, d0) & ~1u) | tag, hmul2(m0[j].y, d0), hmul2(m1[j].x, d1), hmul2(m1[j].y, d1)));
                if (p.zero) __nanosleep(0);
            }
        }
        __syncwarp();
        if (qe.y & 0x8000) asm volatile("fence.acq_rel.gpu;" ::: "memory");
        if (lane == 0) asm volatile("red.relaxed.gpu.global.add.u32 [%0],1;" ::"l"(flags() + (qe.y & 0x7fff)) : "memory");
    }
}

constexpr int EXPORT_LO = 20, EXPORT_N = 31 - EXPORT_LO;
__device__ __forceinline__ uint2 lock64(uint32_t a) {
    uint2 r;
    asm volatile("{.reg .b64 y; atom.shared.exch.b64 y,[%2],0xffffffffffffffff; mov.b64 {%0,%1},y;}" : "=r"(r.x), "=r"(r.y) : "r"(a) : "memory");
    return r;
}

__device__ __forceinline__ void stage3(const Params& p, unsigned char* sm, int g, int o) {
    const int warp = warp_id(), lane = lane_id();
    constexpr uint32_t sb = SB;
    if (threadIdx.x < 64) ((uint32_t*)(sm + SM_AUX + AUX_DUMMY))[threadIdx.x] = ~0u;
    for (int i = (g * NO + o) * 1024 + threadIdx.x; i < NO * (int)SO / 2; i += N3 * 1024) ((uint4*)g_agg)[i] = make_uint4(0, 0, 0, 0);
    __syncthreads();
    if (threadIdx.x == 0) asm volatile("red.release.gpu.global.add.u32 [%0],1;" ::"l"(&g_sync[SY_ZERO]) : "memory");
    const int t0 = p.pairs * 2 * STEP + (g * NO + o) * 1024 + threadIdx.x;
    static_assert(2 * STEP <= N3 * 1024, "remainder");
    if (t0 - lane < p.T) {
        const int t = min(t0, p.T - 1);
        const uint2 v = __ldg(p.m + p.idx_in[t]);
        wait_zeroed();
        if (t0 < p.T) red_agg(p.idx_out[t], v, dup_bf16(cos_any(rbf16(bf_lo(p.freq[0]) * bf_lo(p.angle[t])))));
        __syncwarp();
    }
    constexpr int NCW = 20, STEPS = IG / 4;
    if (warp == 31) {
        poller<NCW, FL_GO3>(sm, g, (XO + o * XSEG) >> 12, (XO + XG) >> 12, p.units, p.units - 2 * N1, [&] {
            constexpr int H = (SO / 2 + 7) & ~7;
            const int e0 = (o * SO + g * H) & ~7, n = min(H + 8, p.E - e0) & ~7;
            if (n > 0 && elect_one()) {
                asm volatile("cp.async.bulk.prefetch.L2.global [%0],%1;" ::"l"(g_agg + e0), "r"(n * 8) : "memory");
                asm volatile("cp.async.bulk.prefetch.L2.global [%0],%1;" ::"l"(p.dist + e0), "r"(n * 2) : "memory");
            }
            __syncwarp();
        });
    } else if (warp < NCW) {
        const uint32_t dummy = sb + SM_AUX + AUX_DUMMY + lane * 8, r0 = (lane & 7) * 2;
        const uint32_t vlane = slot_v(0) + ring_off(0, o * VSEG) + lane * 16, xlane = ring_off(0, XO + o * XSEG) + lane * 4;
        const uint32_t clane = ring_off(0, XO + XG + o * IG) + (lane >> 3) * 4;
        for (int t = warp; t < p.units; t += NCW) {
            uint2 qe;
            next_unit<true>(sb + SM_AUX, warp, t, NCW, qe);
            const uint32_t tag = qe.x >> 31, ab = slot_a((qe.x >> 16) & 0xff);
            const uint4* vp = (const uint4*)(g_ring + (((qe.x >> 24) & 0x7f) * (PV * 8192) + vlane + (((qe.x >> (o >> 1)) & 1) << 12)));
            const uint32_t* xp = (const uint32_t*)(g_ring + (ab + xlane + ((qe.x >> 2) & 0x1000)));
            const uint32_t* cp = (const uint32_t*)(g_ring + (ab + clane + ((qe.x >> 3) & 0x1000)));
            uint4 v[STEPS]; uint32_t x[STEPS];
            const uint32_t cn = __ldcg(cp);
#pragma unroll
            for (int j = 0; j < STEPS; j++) x[j] = __ldcg(xp + j * 32);
#pragma unroll
            for (int j = 0; j < STEPS; j++) v[j] = ld128(vp + j * 32);
            for (int spins = 0;; spins++) {
                uint32_t bad = 0;
#pragma unroll
                for (int j = 0; j < STEPS; j++) bad |= v[j].x ^ tag;
                if (!__any_sync(0xffffffffu, bad & 1)) break;
                if (spins > (1 << 22)) __trap();
#pragma unroll
                for (int j = 0; j < STEPS; j++) v[j] = ld128(vp + j * 32);
            }
            uint32_t ad[2 * STEPS], dep = cn;
#pragma unroll
            for (int j = 0; j < STEPS; j++) {
                const uint32_t c = (cn >> (8 * j)) & 0xff;
                ad[2 * j] = r0 < c ? sb + (x[j] & 0xffff) * 8 : dummy;
                ad[2 * j + 1] = r0 + 1 < c ? sb + (x[j] >> 16) * 8 : dummy;
                dep ^= x[j];
            }
            if (lane == 0) asm volatile("red.relaxed.gpu.global.add.u32 [%0],%1;" ::"l"(flags() + (qe.y & 0x7fff)), "r"(1 + (dep & p.zero)) : "memory");
            uint32_t pend = 0;
#pragma unroll
            for (int j0 = 0; j0 < 2 * STEPS; j0 += 4) {
                uint2 t[4];
#pragma unroll
                for (int j = 0; j < 4; j++) t[j] = lock64(ad[j0 + j]);
#pragma unroll
                for (int j = 0; j < 4; j++) {
                    const int jj = j0 + j;
                    const uint32_t vx = (jj & 1) ? v[jj / 2].z : v[jj / 2].x, vy = (jj & 1) ? v[jj / 2].w : v[jj / 2].y;
                    asm volatile("{.reg .pred p,q; setp.ne.u32 p,%4,0xffffffff; @p st.shared.v2.u32 [%1],{%2,%3}; setp.ne.and.u32 q,%1,%5,!p; @q or.b32 %0,%0,%6;}"
                                 : "+r"(pend) : "r"(ad[jj]), "r"(hadd2(t[j].x, vx)), "r"(hadd2(t[j].y, vy)), "r"(t[j].x), "r"(dummy), "r"(1u << jj) : "memory");
                }
            }
            while (__any_sync(0xffffffffu, pend)) {
                uint32_t a = dummy, vx = 0, vy = 0;
#pragma unroll
                for (int jj = 2 * STEPS - 1; jj >= 0; jj--)
                    if (pend & (1u << jj)) { a = ad[jj]; vx = (jj & 1) ? v[jj / 2].z : v[jj / 2].x; vy = (jj & 1) ? v[jj / 2].w : v[jj / 2].y; }
                const uint2 t = lock64(a);
                asm volatile("{.reg .pred p; setp.ne.u32 p,%4,0xffffffff; @p st.shared.v2.u32 [%1],{%2,%3}; @p and.b32 %0,%0,%5;}"
                             : "+r"(pend) : "r"(a), "r"(hadd2(t.x, vx)), "r"(hadd2(t.y, vy)), "r"(t.x), "r"(pend - 1) : "memory");
            }
        }
    }
    if (warp < NCW) bar_arrive(1, 992);
}

__device__ __forceinline__ void mma_edge(float (&c)[4], uint32_t p01, uint32_t q01, uint32_t p23, uint32_t q23, uint2 b) {
    asm("mma.sync.aligned.m16n8k16.row.col.f32.bf16.bf16.f32 {%0,%1,%2,%3},{%4,%5,%6,%7},{%8,%9},{%0,%1,%2,%3};"
        : "+f"(c[0]), "+f"(c[1]), "+f"(c[2]), "+f"(c[3]) : "r"(p01), "r"(q01), "r"(p23), "r"(q23), "r"(b.x), "r"(b.y));
}
__device__ __forceinline__ uint2 b_frag(const uint16_t* w, int j0) {
    int lane; asm("mov.u32 %0,%%laneid;" : "=r"(lane));
    const int j = j0 + ((lane >> 2) & 1);
    const uint2 v = make_uint2(w[j] | ((uint32_t)w[4 + j] << 16), w[8 + j] | ((uint32_t)w[12 + j] << 16));
    return (lane & 3) == (lane >> 3) ? v : make_uint2(0, 0);
}
__device__ __forceinline__ void edge_gates(const uint16_t* w, uint32_t d2, uint4& sp, uint4& gp) {
    uint32_t rb[2][4];
#pragma unroll
    for (int k = 0; k < 2; k++)
#pragma unroll
        for (int r = 0; r < 4; r++) {
            uint32_t x; asm("sub.rn.bf16x2 %0,%1,%2;" : "=r"(x) : "r"(__byte_perm(d2, 0, k ? 0x3232 : 0x1010)), "r"(((const uint32_t*)w)[48 + r]));
            const uint32_t t = hmul2(hmul2(x, x), 0xc120c120u);
            rb[k][r] = pack2(__expf(bf_lo(t)), __expf(bf_hi(t)));
        }
    uint32_t o[4][2];
#pragma unroll
    for (int n = 0; n < 4; n++) {
        float c[4] = {};
        mma_edge(c, rb[0][0], rb[1][0], rb[0][1], rb[1][1], b_frag(w + (n >> 1) * 32, (n & 1) * 2));
        mma_edge(c, rb[0][2], rb[1][2], rb[0][3], rb[1][3], b_frag(w + (n >> 1) * 32 + 16, (n & 1) * 2));
        o[n][0] = pack2(c[0], c[1]); o[n][1] = pack2(c[2], c[3]);
    }
    gp = make_uint4(o[0][0], o[1][0], o[0][1], o[1][1]);
    sp = make_uint4(o[2][0], o[3][0], o[2][1], o[3][1]);
}
__device__ __forceinline__ uint4 edge_finish(const uint16_t* w, uint4 a, uint4 sp, uint4 gp, uint4 mv) {
    float t0[4] = {}, t1[4] = {}, u0[4] = {}, u1[4] = {};
    mma_edge(t0, a.x, a.z, a.y, a.w, b_frag(w + 64, 0));
    mma_edge(t1, a.x, a.z, a.y, a.w, b_frag(w + 64, 2));
    const uint32_t p01 = pack2(t0[0] * bf_lo(sp.x), t0[1] * bf_hi(sp.x)), p23 = pack2(t1[0] * bf_lo(sp.y), t1[1] * bf_hi(sp.y));
    const uint32_t q01 = pack2(t0[2] * bf_lo(sp.z), t0[3] * bf_hi(sp.z)), q23 = pack2(t1[2] * bf_lo(sp.w), t1[3] * bf_hi(sp.w));
    mma_edge(u0, p01, q01, p23, q23, b_frag(w + 80, 0));
    mma_edge(u1, p01, q01, p23, q23, b_frag(w + 80, 2));
    return make_uint4(hadd2(mv.x, hmul2(pack2(u0[0], u0[1]), gp.x)), hadd2(mv.y, hmul2(pack2(u1[0], u1[1]), gp.y)),
                      hadd2(mv.z, hmul2(pack2(u0[2], u0[3]), gp.z)), hadd2(mv.w, hmul2(pack2(u1[2], u1[3]), gp.w)));
}

__device__ __forceinline__ void finish(const Params& p, unsigned char* sm) {
    __syncwarp();
    const int b = blockIdx.x, tid = threadIdx.x;
    const int role = ((const volatile uint32_t*)(sm + SM_AUX + AUX_MISC))[2];
    const uint16_t* w = (const uint16_t*)(sm + SM_AUX + AUX_W);
    if (role != 3) {
        __syncthreads();
        if (tid == 0) asm volatile("red.release.gpu.global.add.u32 [%0],1;" ::"l"(&g_sync[SY_END]) : "memory");
    }
    constexpr int EP = 3, es = NCTA * 1024;
    static_assert(EP * es * 2 >= E_CAP, "epilogue");
    uint4 sg[2 * EP];
    const int e0 = b * 1024 + tid, np = p.E / 2;
#pragma unroll
    for (int k = 0; k < EP; k++) sg[2 * k].x = __ldg((const uint32_t*)p.dist + min(e0 + k * es, np - 1));
#pragma unroll
    for (int k = 0; k < EP; k++) edge_gates(w, sg[2 * k].x, sg[2 * k], sg[2 * k + 1]);
    uint4 mv[EP];
#pragma unroll
    for (int k = 0; k < EP; k++) mv[k] = __ldg((const uint4*)p.m + min(e0 + k * es, np - 1));
    if (role == 3) {
        const int et = tid - EXPORT_LO * 32;
        if (et >= 0 && et < EXPORT_N * 32) {
            uint4* dst = (uint4*)(g_agg + (((const volatile uint32_t*)(sm + SM_AUX + AUX_MISC))[3] & 255) * SO);
            wait_zeroed();
            __syncwarp();
            bar_sync(1, 992);
#pragma unroll 4
            for (int i = et; i < (int)SO / 2; i += EXPORT_N * 32) {
                const uint4 v = ((const uint4*)sm)[i];
                asm volatile("red.global.add.noftz.v4.bf16x2 [%0],{%1,%2,%3,%4};" ::"l"(dst + i), "r"(v.x), "r"(v.y), "r"(v.z), "r"(v.w) : "memory");
            }
            __syncwarp();
            bar_arrive(2, 1024);
            bar_sync(3, EXPORT_N * 32);
            if (et == 0) asm volatile("red.release.gpu.global.add.u32 [%0],1;" ::"l"(&g_sync[SY_END]) : "memory");
            __syncwarp();
        } else bar_sync(2, 1024);
    }
    uint4* const stash = (uint4*)sm + tid;
#pragma unroll
    for (int k = 0; k < EP; k++) { stash[(3 * k) * 1024] = sg[2 * k]; stash[(3 * k + 1) * 1024] = sg[2 * k + 1]; stash[(3 * k + 2) * 1024] = mv[k]; }
    if (tid == 0) {
        wait_flag(&g_sync[SY_END], NCTA);
        asm volatile("fence.acquire.gpu;" ::: "memory");
    }
    __syncthreads();
    uint4 av[EP];
#pragma unroll
    for (int k = 0; k < EP; k++) av[k] = __ldcg((const uint4*)g_agg + min(e0 + k * es, np - 1));
#pragma unroll
    for (int k = 0; k < EP; k++) {
        const uint4 o = edge_finish(w, av[k], stash[(3 * k) * 1024], stash[(3 * k + 1) * 1024], stash[(3 * k + 2) * 1024]);
        if (e0 + k * es < np) ((uint4*)p.out)[e0 + k * es] = o;
    }
    if (b == 0 && tid < 512) ((uint4*)flags())[tid] = make_uint4(0, 0, 0, 0);
    if (tid == 0) {
        g_info[b] = make_uint2(0, 0);
        if (atomicAdd(&g_sync[SY_EXIT], 1) == NCTA - 1)
            g_sync[SY_ZERO] = g_sync[SY_END] = g_sync[SY_EXIT] = g_sync[SY_WORK] = g_sync[SY_LOG] = g_sync[SY_LOG + 1] = 0;
    }
}

__global__ void __launch_bounds__(1024, 1) main_kernel(const __grid_constant__ Params p) {
    extern __shared__ __align__(128) unsigned char sm[];
    const int b = blockIdx.x, tid = threadIdx.x, warp = tid >> 5;
    if ((uint32_t)__cvta_generic_to_shared(sm) != SB) __trap();
    uint32_t* s_misc = (uint32_t*)(sm + SM_AUX + AUX_MISC);
    if (tid == 0) s_misc[0] = s_misc[4] = s_misc[5] = 0;
    __syncthreads();
    if ((tid & 31) == 0) {
        const int sl = b * 2 + (warp >> 4), j = warp & 15;
        if (warp == 31) s_misc[1] = upper_is_near(g_probe + (b & 127) * 32);
        else if (sl < NSL && j < (sl < KA ? PA : sl < KA + KV ? PV : 1) &&
                 upper_is_near(g_ring + (sl < KA ? slot_a(sl) : slot_v(sl - KA)) + j * 8192 + 4064))
            atomicOr(&s_misc[0], 1u << warp);
    }
    __syncwarp();
    __syncthreads();
    uint32_t me; asm("mov.u32 %0,%%smid;" : "=r"(me));
    me = 0x8000u | (s_misc[1] << 14) | (me & 0x3fff);
    if (tid == 0) {
        const u64 v = (u64)(s_misc[0] ^ (s_misc[1] ? ~0u : 0u)) | ((u64)me << 32);
        asm volatile("st.release.gpu.global.u64 [%0],%1;" ::"l"(&g_info[b]), "l"(v) : "memory");
    }
    for (int i = tid; i < (SM_AUX + AUX_CLS) / 16; i += 1024) ((uint4*)sm)[i] = make_uint4(0, 0, 0, 0);
    uint16_t* w = (uint16_t*)(sm + SM_AUX + AUX_W);
    if (tid < 160) {
        u64 v = 0; int spins = 0;
        while (tid < NCTA && !(v >> 32)) {
            asm volatile("ld.acquire.gpu.global.u64 %0,[%1];" : "=l"(v) : "l"(&g_info[tid]) : "memory");
            if (++spins > (1 << 22)) __trap();
        }
        __syncwarp();
        if (tid < NCTA) ((uint32_t*)(sm + SM_AUX + AUX_CLS))[tid] = (uint32_t)v;
        const uint32_t o = v >> 32;
        const uint32_t c = __reduce_add_sync(0xffffffffu, tid < NCTA ? 1u << (8 * ((o & 1) | ((o >> 13) & 2))) : 0u);
        const uint32_t r = __popc(__ballot_sync(0xffffffffu, tid < NCTA && ((o ^ me) & 0x4001) == 0 && (o > me || (o == me && tid > b))));
        if ((tid & 31) == 0) { atomicAdd(&s_misc[4], c); atomicAdd(&s_misc[5], r); }
    } else if (tid >= 256 && tid < 256 + 104) {
        const int j = tid - 256;
        w[j] = j < 32 ? p.w_rbf[j] : j < 64 ? p.w_sbf[j - 32] : j < 80 ? p.w_down[j - 64] : j < 96 ? p.w_up[j - 80] : p.centers[j - 96];
    }
    __syncthreads();
    int role, rank;
    {
        const uint32_t cnt = s_misc[4], cl = (me & 1) | ((me >> 13) & 2);
        rank = s_misc[5];
        const int c2 = (rank + 1) * IG / NO;
        if (__vminu4(cnt, NO * 0x01010101u) != NO * 0x01010101u) {
            role = b < N2 ? 2 : b < N2 + N3 ? 3 : 1;
            const int r = role == 2 ? b : b - N2;
            rank = role == 1 ? b - N2 - N3 : (r >> 1) | ((r & 1) << 8);
        } else if (rank < NO && (me & 1)) { role = 3; rank |= (cl >> 1) << 8; }
        else if (rank < NO && c2 != rank * IG / NO) { role = 2; rank = (c2 - 1) | ((cl >> 1) << 8); }
        else {
            role = 1;
            rank -= (me & 1) ? NO : min(c2, IG);
            for (uint32_t c = 0; c < cl; c++) rank += ((cnt >> (8 * c)) & 0xff) - ((c & 1) ? NO : IG);
        }
        if (tid == 0) { s_misc[2] = role; s_misc[3] = rank; }
    }
    if (role == 1) stage1(p, sm, rank);
    else if (role == 2) stage2(p, sm, rank >> 8, rank & 255);
    else stage3(p, sm, rank >> 8, rank & 255);
    finish(p, sm);
}

__global__ void generic_scatter(const __grid_constant__ Params p) {
    const float f = bf_lo(p.freq[0]);
    for (int t = blockIdx.x * blockDim.x + threadIdx.x; t < p.T; t += gridDim.x * blockDim.x) {
        const uint2 v = __ldg(p.m + p.idx_in[t]);
        const uint32_t c2 = dup_bf16(cos_any(rbf16(f * bf_lo(p.angle[t]))));
        asm volatile("red.global.add.noftz.v2.bf16x2 [%0],{%1,%2};" ::"l"(p.out + p.idx_out[t]), "r"(hmul2(v.x, c2)), "r"(hmul2(v.y, c2)) : "memory");
    }
}
__global__ void __launch_bounds__(256) generic_finish(const __grid_constant__ Params p) {
    __shared__ __align__(16) uint16_t w[104];
    const int j = threadIdx.x, e = blockIdx.x * blockDim.x + j, ec = min(e, p.E - 1);
    if (j < 104) w[j] = j < 32 ? p.w_rbf[j] : j < 64 ? p.w_sbf[j - 32] : j < 80 ? p.w_down[j - 64] : j < 96 ? p.w_up[j - 80] : p.centers[j - 96];
    const uint2 a = p.out[ec], mv = p.m[ec];
    __syncthreads();
    uint4 s0, s1;
    edge_gates(w, p.dist[ec] * 0x10001u, s0, s1);
    const uint4 o = edge_finish(w, make_uint4(a.x, a.y, a.x, a.y), s0, s1, make_uint4(mv.x, mv.y, mv.x, mv.y));
    if (e < p.E) p.out[e] = make_uint2(o.x, o.y);
}

extern "C" void kernel_launch(void* const* d_in, const int* in_sizes, int n_in, void* d_out, int out_size) {
    static int nsm = 0;
    if (!nsm) {
        cudaDeviceGetAttribute(&nsm, cudaDevAttrMultiProcessorCount, 0);
        cudaFuncSetAttribute(main_kernel, cudaFuncAttributeMaxDynamicSharedMemorySize, SMEM_BYTES);
    }
    Params p;
    p.m = (const uint2*)d_in[0]; p.idx_in = (const int*)d_in[1]; p.idx_out = (const int*)d_in[2];
    p.angle = (const uint16_t*)d_in[4]; p.freq = (const uint16_t*)d_in[6];
    p.dist = (const uint16_t*)d_in[3]; p.centers = (const uint16_t*)d_in[5]; p.w_rbf = (const uint16_t*)d_in[7];
    p.w_sbf = (const uint16_t*)d_in[8]; p.w_down = (const uint16_t*)d_in[9]; p.w_up = (const uint16_t*)d_in[10];
    p.out = (uint2*)d_out;
    p.E = in_sizes[3]; p.T = in_sizes[1];
    p.zero = 0;
    p.pairs = p.T / (2 * STEP); p.units = p.pairs + (NR / 2 + 1) * N1;
    bool fast = nsm >= NCTA && p.E <= E_CAP && p.E >= 8 && p.E % 2 == 0 && p.pairs >= 2 * N1 && p.units < 0xff00;
    static cudaTextureObject_t tex[3];
    static const void* tex_ptr[3];
    static int tex_n[3];
    for (int k = 0; k < 3 && fast; k++) {
        void* ptr = d_in[k == 2 ? 4 : 1 + k];
        if (tex_ptr[k] == ptr && tex_n[k] == p.T) continue;
        cudaResourceDesc rd = {};
        rd.resType = cudaResourceTypeLinear;
        rd.res.linear.devPtr = ptr;
        rd.res.linear.desc = k == 2 ? cudaCreateChannelDesc<uint2>() : cudaCreateChannelDesc<uint4>();
        rd.res.linear.sizeInBytes = (size_t)(p.T / 4) * (k == 2 ? 8 : 16);
        cudaTextureDesc td = {};
        td.readMode = cudaReadModeElementType;
        if (cudaCreateTextureObject(&tex[k], &rd, &td, nullptr) == cudaSuccess) { tex_ptr[k] = ptr; tex_n[k] = p.T; }
        else { cudaGetLastError(); tex_ptr[k] = nullptr; fast = false; }
    }
    p.tin = tex[0]; p.tout = tex[1]; p.tang = tex[2];
    if (!fast) {
        cudaMemsetAsync(d_out, 0, (size_t)p.E * 8);
        generic_scatter<<<nsm * 8, 256>>>(p);
        generic_finish<<<(p.E + 255) / 256, 256>>>(p);
        return;
    }
    void* args[] = {&p};
    cudaLaunchCooperativeKernel((const void*)main_kernel, dim3(NCTA), dim3(1024), args, SMEM_BYTES, cudaStreamPerThread);
}
```

```cpp
#include <cuda_runtime.h>
#include <cuda_bf16.h>
#include <stdint.h>

typedef unsigned long long u64;
constexpr uint32_t magic_of(uint32_t d) { return (uint32_t)(((1ull << 32) + d - 1) / d); }
constexpr uint32_t slice_of(uint32_t total, uint32_t n) {
    uint32_t d = ((total + n - 1) / n + 1) & ~1u;
    while (!((uint64_t)(n * d - 1) * magic_of(d) < ((uint64_t)n << 32))) d += 2;
    return d;
}
constexpr int E_CAP = 800000;
constexpr int NI = 32, NO = 28, NG = 2, IG = NI / NG;
constexpr uint32_t SI = slice_of(E_CAP, NI), SO = slice_of(E_CAP, NO);
constexpr uint32_t MI = magic_of(SI), MO = magic_of(SO);
constexpr int NCTA = 132, N2 = NI, N3 = NO * NG, N1 = NCTA - N2 - N3;
constexpr int C = 16, GB = NO * IG;
constexpr int NP = 5;
constexpr int NW = 28, STEP = NW * 256;
constexpr int NR = 4, LOGCAP = 8192, NCH = N1 * NW * NR * 8, KMAX = 4000;
static_assert(NR % 2 == 0 && NR >= 2 && NR <= 4 && NO % 4 == 0 && IG == 16, "shape");

constexpr int DA = 3, DS = 2, DV = 2, KA = DA * N1, KV = DV * N1, NSL = KA + KV + 1;
constexpr int ASEG = NO * C * 4, XSEG = IG * C * 2, VSEG = IG * C * 8;
constexpr int AG = IG * ASEG, XG = NO * XSEG, XO = IG / 2 * 4096, AXG = XO + XG + GB;
constexpr int PA = (AXG + 4095) / 4096, PV = NO * VSEG / 4096;
static_assert(2 * ASEG <= 4096 && AG == 2 * XG && (XO + XG) / 4096 == (AXG - 1) / 4096 && PA <= 15 && PV <= 14, "layout");
static_assert(DS >= DA - DV && DS <= DA && KA <= 256 && KV <= 128 && NSL <= 2 * NCTA && N1 <= 64, "ring");

constexpr uint32_t SB = 1024;
constexpr int SM_CNT = 0, SM_CB = NG * GB * 4, SM_LC = SM_CB + 2 * GB, SM_X = SM_LC + 256, SM_A = SM_X + NP * XG,
              SM_S1_END = SM_A + NP * AG;
constexpr int SM_AUX = SO * 8 + 512, QN = 256;
constexpr int AUX_Q = 0, AUX_PROG = QN * 8, AUX_CLS = AUX_PROG + 128, AUX_MISC = AUX_CLS + 576, AUX_DUMMY = AUX_MISC + 32,
              AUX_W = AUX_DUMMY + 256, AUX_END = AUX_W + 208;
constexpr int SMEM_BYTES = SM_AUX + AUX_END;
static_assert(SM_S1_END + 256 + NW * 256 <= SM_AUX && SMEM_BYTES <= 232448 && SM_X % 128 == 0 && AUX_W % 16 == 0, "smem");

__device__ __align__(8192) unsigned char g_ring[(size_t)(KA * PA + KV * PV + 1) * 8192];
__device__ __align__(8192) unsigned char g_probe[8192];
__device__ uint2 g_log[N1 * NW * LOGCAP];
__device__ uint32_t g_chunks[NCH];
__device__ __align__(128) uint2 g_agg[NO * SO];
__device__ uint2 g_info[NCTA];
__device__ __align__(128) uint32_t g_sync[160];
constexpr int SY_ZERO = 0, SY_END = 32, SY_EXIT = 64, SY_WORK = 96, SY_LOG = 128;
constexpr int FL_GO2 = 0, FL_GO3 = 1;
constexpr uint32_t FL_DATA = 0x10000;

__device__ __forceinline__ int lane_id() { int v; asm volatile("mov.u32 %0,%%laneid;" : "=r"(v)); return v; }
__device__ __forceinline__ int warp_id() { int v; asm volatile("mov.u32 %0,%%tid.x;" : "=r"(v)); return __shfl_sync(0xffffffffu, v >> 5, 0); }
__device__ __forceinline__ float bf_lo(uint32_t v) { return __uint_as_float(v << 16); }
__device__ __forceinline__ float bf_hi(uint32_t v) { return __uint_as_float(v & 0xffff0000u); }
__device__ __forceinline__ float rbf16(float x) { return __bfloat162float(__float2bfloat16_rn(x)); }
__device__ __forceinline__ uint32_t hmul2(uint32_t a, uint32_t b) {
    uint32_t d; asm("mul.rn.bf16x2 %0,%1,%2;" : "=r"(d) : "r"(a), "r"(b)); return d;
}
__device__ __forceinline__ uint32_t hadd2(uint32_t a, uint32_t b) {
    uint32_t d; asm("add.rn.bf16x2 %0,%1,%2;" : "=r"(d) : "r"(a), "r"(b)); return d;
}
__device__ __forceinline__ uint32_t dup_bf16(float x) {
    uint32_t d; asm("cvt.rn.bf16x2.f32 %0,%1,%1;" : "=r"(d) : "f"(x)); return d;
}
__device__ __forceinline__ uint32_t pack2(float lo, float hi) {
    uint32_t d; asm("cvt.rn.bf16x2.f32 %0,%2,%1;" : "=r"(d) : "f"(lo), "f"(hi)); return d;
}
__device__ __noinline__ float cos_slow(float x) { return cosf(x); }
__device__ __forceinline__ float cos_any(float x) { return fabsf(x) < 32.f ? __cosf(x) : cos_slow(x); }
__device__ __forceinline__ void bar_sync(int id, int n) { asm volatile("barrier.sync.aligned %0,%1;" ::"r"(id), "r"(n) : "memory"); }
__device__ __forceinline__ void bar_arrive(int id, int n) { asm volatile("barrier.arrive.aligned %0,%1;" ::"r"(id), "r"(n) : "memory"); }
__device__ __forceinline__ uint32_t ld_relaxed(const uint32_t* p) {
    uint32_t v; asm volatile("ld.relaxed.gpu.global.u32 %0,[%1];" : "=r"(v) : "l"(p) : "memory"); return v;
}
__device__ __forceinline__ void st128(void* p, uint4 v) {
    asm volatile("{.reg .b64 a,b; .reg .b128 q; mov.b64 a,{%1,%2}; mov.b64 b,{%3,%4}; mov.b128 q,{a,b}; st.relaxed.gpu.global.b128 [%0],q;}" ::"l"(p), "r"(v.x), "r"(v.y), "r"(v.z), "r"(v.w) : "memory");
}
__device__ __forceinline__ uint4 ld128(const void* p) {
    uint4 v;
    asm volatile("{.reg .b64 a,b; .reg .b128 q; ld.relaxed.gpu.global.b128 q,[%4]; mov.b128 {a,b},q; mov.b64 {%0,%1},a; mov.b64 {%2,%3},b;}" : "=r"(v.x), "=r"(v.y), "=r"(v.z), "=r"(v.w) : "l"(p) : "memory");
    return v;
}
__device__ __forceinline__ void wait_flag(const uint32_t* p, uint32_t want) {
    int spins = 0;
    while ((ld_relaxed(p) & 0xffff) < want) {
        __nanosleep(100);
        if (++spins > (1 << 22)) __trap();
    }
}
__device__ __forceinline__ uint32_t slot_a(int s) { return s * (PA * 8192); }
__device__ __forceinline__ uint32_t slot_v(int s) { return KA * PA * 8192 + s * (PV * 8192); }
__device__ __forceinline__ uint32_t ring_off(uint32_t clsg, uint32_t off) {
    return ((off >> 12) << 13) + (((clsg >> (off >> 12)) & 1) << 12) + (off & 4095);
}
__device__ __forceinline__ uint32_t cls_of(const unsigned char* sm, int s, int g) {
    return ((const uint16_t*)(sm + SM_AUX + AUX_CLS))[s] ^ (g ? ~0u : 0u);
}
__device__ __forceinline__ uint32_t flag_idx(const unsigned char* sm, int g, int type, int q) {
    return ring_off(cls_of(sm, NSL - 1, g), type * 1024 + q * 8) / 4;
}
__device__ __forceinline__ uint32_t* flags() { return (uint32_t*)(g_ring + slot_v(KV)); }
__device__ __forceinline__ uint32_t arrivals(int type, uint32_t k) {
    static_assert(DV == 2, "flag ring");
    return type == FL_GO3 ? IG * ((k >> 1) + 1) : NO * (k >> 1);
}
__device__ __forceinline__ bool elect_one() {
    uint32_t r; asm volatile("{.reg .pred p; elect.sync _|p,0xffffffff; selp.u32 %0,1,0,p;}" : "=r"(r)); return r;
}
template <int NCW, int TYPE, class F>
__device__ __forceinline__ void poller(const unsigned char* sm, int g, int blk0, int blk1, int units, int hook_at, F hook) {
    const int lane = lane_id();
    constexpr uint32_t aux = SB + SM_AUX;
    constexpr int DR = TYPE == FL_GO2 ? DS : DA;
    const uint32_t lt = (1u << lane) - 1;
    uint32_t ea[2][DR], ev[2][DV], k[2] = {0, 0}, want[2], v[2], fin[2], fout[2];
#pragma unroll
    for (int j = 0; j < 2; j++) {
        const int q = min(lane + j * 32, N1 - 1);
#pragma unroll
        for (int d = 0; d < DR; d++) {
            const uint32_t sa = q + d * N1, ca = cls_of(sm, sa, g);
            ea[j][d] = (((ca >> blk0) & 1) << 14) | (((ca >> blk1) & 1) << 15) | (sa << 16);
        }
#pragma unroll
        for (int d = 0; d < DV; d++) ev[j][d] = (cls_of(sm, KA + q + d * N1, g) & 0x3fff) | ((q + d * N1) << 24);
        want[j] = lane + j * 32 < N1 ? FL_DATA + arrivals(TYPE, 0) : ~0u;
        v[j] = 0;
        fin[j] = flag_idx(sm, g, TYPE, q); fout[j] = flag_idx(sm, g, TYPE ^ 1, q);
    }
    int tail = 0, check = min(min(QN - N1, hook_at), units), spins = 0;
    while (true) {
        bool hit[2]; uint32_t bal[2];
#pragma unroll
        for (int j = 0; j < 2; j++) {
            hit[j] = v[j] >= want[j] && (uint16_t)v[j] >= (uint16_t)want[j];
            bal[j] = __ballot_sync(0xffffffffu, hit[j]);
        }
        if (bal[0] | bal[1]) {
            asm volatile("fence.acquire.gpu;" ::: "memory");
            if (TYPE == FL_GO2) asm volatile("fence.proxy.async.global;" ::: "memory");
            asm volatile("fence.acq_rel.cta;" ::: "memory");
            spins = 0;
        } else if (++spins > (1 << 22)) __trap();
#pragma unroll
        for (int j = 0; j < 2; j++) {
            const uint32_t pos = tail + __popc(bal[j] & lt);
            const uint32_t hi = fout[j] | (k[j] & 1) | (k[j] < DV ? 0x8000 : 0) | ((pos + 1) << 16);
            asm volatile("{.reg .pred p; .reg .b64 q; setp.ne.u32 p,%3,0; mov.b64 q,{%1,%2}; @p st.relaxed.cta.shared.u64 [%0],q;}"
                         ::"r"(aux + AUX_Q + (pos % QN) * 8), "r"(ea[j][0] | ev[j][0]), "r"(hi), "r"((uint32_t)hit[j]) : "memory");
            tail += __popc(bal[j]);
            k[j] += hit[j];
        }
#pragma unroll
        for (int j = 0; j < 2; j++) v[j] = ld_relaxed(flags() + (fin[j] | (k[j] & 1)));
#pragma unroll
        for (int j = 0; j < 2; j++) {
            const uint32_t a0 = ea[j][0], v0 = ev[j][0] ^ 0x80000000u;
#pragma unroll
            for (int d = 0; d < DR; d++) ea[j][d] = hit[j] ? (d + 1 < DR ? ea[j][(d + 1) % DR] : a0) : ea[j][d];
#pragma unroll
            for (int d = 0; d < DV; d++) ev[j][d] = hit[j] ? (d + 1 < DV ? ev[j][(d + 1) % DV] : v0) : ev[j][d];
            want[j] = hit[j] ? ((k[j] >> 1) + 1) * FL_DATA + arrivals(TYPE, k[j]) : want[j];
        }
        if (tail >= check) {
            if (tail >= units) break;
            if (tail >= hook_at) { hook(); hook_at = 0x7fffffff; }
            int limit;
            do {
                int prog; asm volatile("ld.volatile.shared.u32 %0,[%1];" : "=r"(prog) : "r"(aux + AUX_PROG + min(lane, NCW - 1) * 4) : "memory");
                limit = __reduce_min_sync(0xffffffffu, prog) + QN - N1;
            } while (tail > limit);
            check = min(min(limit, hook_at), units);
        }
    }
}
template <bool BLOCK>
__device__ __forceinline__ bool next_unit(uint32_t aux, int warp, int t, int step, uint2& e) {
    u64 v;
    while (true) {
        asm volatile("ld.acquire.cta.shared.u64 %0,[%1];" : "=l"(v) : "r"(aux + AUX_Q + (t % QN) * 8) : "memory");
        if (__all_sync(0xffffffffu, (int)(v >> 48) == t + 1)) break;
        if (!BLOCK) return false;
        __nanosleep(40);
    }
    if (((t + step) ^ t) & 64) asm volatile("st.volatile.shared.u32 [%0],%1;" ::"r"(aux + AUX_PROG + warp * 4), "r"(t + step) : "memory");
    e = make_uint2((uint32_t)v, (uint32_t)(v >> 32) & 0xffff);
    return true;
}
__device__ __forceinline__ int upper_is_near(unsigned char* q) {
    ((uint4*)q)[0] = ((uint4*)q)[1] = ((uint4*)(q + 4096))[0] = ((uint4*)(q + 4096))[1] = make_uint4(0, 0, 0, 0);
    uint32_t best[2] = {~0u, ~0u};
#pragma unroll
    for (int r = 0; r < 4; r++) {
        uint32_t t0, t1, v;
        asm volatile("mov.u32 %0,%%clock;" : "=r"(t0)::"memory");
        asm volatile("atom.global.exch.b32 %0,[%1],0;" : "=r"(v) : "l"(q + (r & 1) * 4096) : "memory");
        asm volatile("{.reg .pred p; setp.eq.u32 p,%1,0xffffffff; @p trap; mov.u32 %0,%%clock;}" : "=r"(t1) : "r"(v) : "memory");
        best[r & 1] = min(best[r & 1], t1 - t0);
    }
    return best[1] < best[0];
}

struct Params {
    const uint2* m; const int* idx_in; const int* idx_out; const uint16_t* angle; const uint16_t* freq;
    const uint16_t *dist, *centers, *w_rbf, *w_sbf, *w_down, *w_up; uint2* out;
    int E, T, pairs, units;
    uint32_t zero;
    cudaTextureObject_t tin, tout, tang;
};

__device__ __forceinline__ void red_agg(uint32_t out, uint2 v, uint32_t c2) {
    asm volatile("red.global.add.noftz.v2.bf16x2 [%0],{%1,%2};" ::"l"(g_agg + out), "r"(hmul2(v.x, c2)), "r"(hmul2(v.y, c2)) : "memory");
}
__device__ __forceinline__ void decode_entry(uint32_t e0, uint32_t e1, uint32_t& in, uint32_t& out) {
    const uint32_t bx = e1 >> 21, g = bx >= GB, rem = bx - g * GB;
    in = (g * IG + rem % IG) * SI + (e0 & 0xffff);
    out = rem / IG * SO + (e1 & 0xffff);
}
__device__ __forceinline__ void wait_zeroed() {
    wait_flag(&g_sync[SY_ZERO], N3);
    asm volatile("fence.acquire.gpu;" ::: "memory");
}
constexpr int BAR_ATOMS = 1, BAR_STS = 2, BAR_PUB = 4, BAR_PUBFREE = 6, BAR_W = 8, BAR_LOG = 9;
constexpr int NT_STS = (NW + 2) * 32, NT_ATOMS = (NW + 1) * 32;
__device__ __forceinline__ void mbar_arrive(uint32_t bar) {
    __syncwarp();
    if (elect_one()) asm volatile("mbarrier.arrive.shared::cta.b64 _,[%0];" ::"r"(bar) : "memory");
}
__device__ __forceinline__ void mbar_wait(uint32_t bar, uint32_t parity) {
    asm volatile("{.reg .pred p; .reg .u32 n; mbarrier.try_wait.parity.shared::cta.b64 p,[%0],%1; @p bra D; mov.u32 n,0;\n"
                 "W: mbarrier.try_wait.parity.shared::cta.b64 p,[%0],%1,2000; @p bra D;\n"
                 "add.u32 n,n,1; setp.lt.u32 p,n,0x4000000; @p bra W; trap;\nD:}" ::"r"(bar), "r"(parity) : "memory");
}
__device__ __forceinline__ uint32_t mad(uint32_t a, uint32_t b, uint32_t c) {
    uint32_t d; asm("mad.lo.u32 %0,%1,%2,%3;" : "=r"(d) : "r"(a), "r"(b), "r"(c)); return d;
}
template <bool R, int G> struct Kind { static constexpr bool replay = R; static constexpr int group = G; };

__device__ __forceinline__ void stage1(const Params& p, unsigned char* sm, int pid) {
    const int warp = warp_id(), lane = lane_id();
    constexpr uint32_t sb = SB;
    uint4 ra[2], rb[2]; uint2 rc[2];
    volatile int* const s_next = (volatile int*)(sm + SM_LC + 64);
    const int total = p.pairs * 2, snap = total - 2 * 2 * N1, sw = pid & 1;
    u64* const logsync = (u64*)&g_sync[SY_LOG];
    constexpr uint32_t mb = sb + SM_LC;
    if (threadIdx.x < 4) asm volatile("mbarrier.init.shared::cta.b64 [%0],1;" ::"r"(mb + threadIdx.x * 8) : "memory");
    if (threadIdx.x == 0) s_next[2] = s_next[3] = 0x7ffffff0;
    if (threadIdx.x < 32) s_next[16 + threadIdx.x] = 2 * C;
    __syncthreads();
    if (warp < NW) {
        constexpr uint32_t cb = sb + SM_CNT, xdum = (uint32_t)(SM_LC + 128 - SM_CNT) << 19;
        constexpr uint32_t xk = sb + SM_X, ak = sb + SM_A - 2 * xk;
        uint32_t cur0 = xk + sw * XG + (lane & p.zero), nxt0 = cur0 + 2 * XG - C * 2, cur1 = cur0 - sw * 2 * XG, nxt1 = cur1 + 2 * XG - C * 2;
        uint32_t fresh = xk + 4 * XG - C * 2 + (lane & p.zero), n0 = 0, wpos = 0, chunk = 0;
        int h_in = pid * 2, np = 0;
        uint2* const log = g_log + (pid * NW + warp) * LOGCAP;
        const uint32_t ltmask = ((1u << lane) - 1) | p.zero, tq = (warp * 64 + lane) | p.zero;
        auto load_in = [&](int h) {
            const int q = h_in * (STEP / 4) + tq + h * 32;
            asm volatile("tex.1d.v4.u32.s32 {%0,%1,%2,%3},[%4,{%5}];" : "=r"(ra[h].x), "=r"(ra[h].y), "=r"(ra[h].z), "=r"(ra[h].w) : "l"(p.tin), "r"(q));
            asm volatile("tex.1d.v4.u32.s32 {%0,%1,%2,%3},[%4,{%5}];" : "=r"(rb[h].x), "=r"(rb[h].y), "=r"(rb[h].z), "=r"(rb[h].w) : "l"(p.tout), "r"(q));
            asm volatile("{.reg .b32 z,w; tex.1d.v4.u32.s32 {%0,%1,z,w},[%2,{%3}];}" : "=r"(rc[h].x), "=r"(rc[h].y) : "l"(p.tang), "r"(q));
        };
        const uint32_t stage = sb + SM_S1_END + 256 + warp * 256;
        auto flush_stage = [&]() {
            uint2 e;
            __syncwarp();
            asm volatile("ld.shared.v2.u32 {%0,%1},[%2];" : "=r"(e.x), "=r"(e.y) : "r"(stage + lane * 8) : "memory");
            log[(wpos & ~31u) + lane] = e;
            __syncwarp();
        };
        auto direct = [&](uint32_t first, uint32_t stride, uint32_t count, auto range, auto gate) {
            const float f = bf_lo(p.freq[0]);
            for (uint32_t c0 = first;; c0 += stride * 4) {
                uint2 e[4], v[4]; uint32_t ok = 0, big = 0;
#pragma unroll
                for (int k = 0; k < 4; k++) {
                    uint32_t lo = 0, hi = 0;
                    if (c0 + k * stride < count) range(c0 + k * stride, lo, hi);
                    e[k] = make_uint2(0, 0);
                    if (lo + lane < hi) { e[k] = __ldcg(g_log + lo + lane); ok |= 1u << k; }
                }
                __syncwarp();
                if (c0 == first) gate();
#pragma unroll
                for (int k = 0; k < 4; k++) {
                    uint32_t in;
                    decode_entry(e[k].x, e[k].y, in, e[k].y);
                    v[k] = __ldcg(p.m + in);
                    e[k].x = __float_as_uint(rbf16(f * bf_hi(e[k].x)));
                    big = max(big, e[k].x & 0x7fffffffu);
                }
                const bool slow = __any_sync(0xffffffffu, big >= 0x42000000u);
#pragma unroll
                for (int k = 0; k < 4; k++) {
                    float c = __cosf(__uint_as_float(e[k].x));
                    if (slow) c = cos_slow(__uint_as_float(e[k].x));
                    if ((ok >> k) & 1) red_agg(e[k].y, v[k], dup_bf16(c));
                }
                __syncwarp();
                if (c0 + stride * 4 >= count) break;
            }
        };
        auto drain = [&]() {
            const uint32_t lb = (pid * NW + warp) * LOGCAP;
            if (wpos & 31) flush_stage();
            direct(0, 1, (wpos - n0 + 31) / 32, [&](uint32_t c, uint32_t& lo, uint32_t& hi) { lo = lb + n0 + c * 32; hi = lb + wpos; },
                   [&] { wait_zeroed(); __syncwarp(); });
            wpos = n0;
        };
        auto load_log = [&](int j) {
            uint2 e[8];
#pragma unroll
            for (int k = 0; k < 8; k++) {
                const uint32_t ch = __shfl_sync(0xffffffffu, chunk, k * NR + j);
                e[k] = make_uint2(0, xdum + (lane << 21));
                if (j < NR && ch) e[k] = __ldcg(g_log + (ch - 1) * 32 + lane);
            }
#pragma unroll
            for (int h = 0; h < 2; h++) {
                ra[h] = make_uint4(e[h * 4].x, e[h * 4].y, e[h * 4 + 1].x, e[h * 4 + 1].y);
                rb[h] = make_uint4(e[h * 4 + 2].x, e[h * 4 + 2].y, e[h * 4 + 3].x, e[h * 4 + 3].y);
            }
        };
        auto step = [&](const int k2, auto kind) {
            constexpr bool R = decltype(kind)::replay;
            constexpr int G = decltype(kind)::group;
            uint32_t pa[8], aw[8], xw[8], r[8];
#pragma unroll
            for (int h = 0; h < 2; h++) {
                if (!R) {
                    const uint32_t in[4] = {ra[h].x, ra[h].y, ra[h].z, ra[h].w}, out[4] = {rb[h].x, rb[h].y, rb[h].z, rb[h].w};
#pragma unroll
                    for (int k = 0; k < 4; k++) {
                        const uint32_t i = __umulhi(in[k], MI), o = __umulhi(out[k], MO);
                        aw[h * 4 + k] = __byte_perm(in[k] - i * SI, k < 2 ? rc[h].x : rc[h].y, (k & 1) ? 0x7610 : 0x5410);
                        pa[h * 4 + k] = mad(i, NO, o);
                        xw[h * 4 + k] = mad(i, 1u << 21, mad(o, (IG << 21) - SO, out[k]));
                        asm("{.reg .pred p; setp.ge.u32 p,%1,%2; @p add.u32 %0,%0,%3;}" : "+r"(xw[h * 4 + k]) : "r"(in[k]), "n"(IG * SI), "n"((GB - IG) << 21));
                    }
                } else {
#pragma unroll
                    for (int k = h * 4; k < h * 4 + 4; k++) {
                        const uint4 q4 = (k & 2) ? rb[h] : ra[h];
                        const uint2 e = (k & 1) ? make_uint2(q4.z, q4.w) : make_uint2(q4.x, q4.y);
                        aw[k] = e.x; xw[k] = e.y;
                        pa[k] = mad((e.y >> 21) % IG, NO, (e.y >> 25) + (e.y >= GB << 21 ? GB - NO : 0));
                    }
                }
                if (h == 0) {
                    mbar_wait(mb + G * 8, k2 & 1);
                    if (!R) {
                        if (G) asm volatile("ld.volatile.shared.u32 %0,[%1];" : "=r"(h_in) : "r"(mb + 64) : "memory");
                        else h_in++;
                    }
                }
#pragma unroll
                for (int k = h * 4; k < h * 4 + 4; k++)
                    asm volatile("atom.shared.add.u32 %0,[%1+%2],1;" : "=r"(r[k]) : "r"(xw[k] >> 19), "n"(cb) : "memory");
            }
            bar_arrive(BAR_ATOMS, NT_ATOMS);
            mbar_wait(mb + 16 + G * 8, k2 & 1);
            if (!R) {
                load_in(0);
                if (p.zero) __nanosleep(0);
            }
            uint32_t ovf = 0;
#pragma unroll
            for (int k = 0; k < 8; k++) {
                const bool lo = r[k] < C, hi = xw[k] >= GB << 21;
                const uint32_t s2 = r[k] * 2 + (hi ? (lo ? cur1 : nxt1) : (lo ? cur0 : nxt0));
                asm volatile("{.reg .pred p; .reg .b16 a,b; setp.lt.u32 p,%5,%6; mov.b32 {a,b},%4;"
                             " @p st.shared.u32 [%1+%8],%2; @p st.shared.u16 [%3],a; @!p or.b32 %0,%0,%7;}"
                             : "+r"(ovf) : "r"(mad(pa[k], C * 2, s2) * 2), "r"(aw[k]), "r"((xw[k] >> 16) + s2), "r"(xw[k]), "r"(r[k]),
                               "n"(2 * C), "r"(R && xw[k] >= xdum ? 0u : 1u << k), "n"(ak) : "memory");
            }
            bar_arrive(BAR_STS + G, NT_STS);
            if (!R) {
                if (p.zero) __nanosleep(0);
                load_in(1);
            }
            uint32_t bal = __ballot_sync(0xffffffffu, ovf != 0);
            while (bal) {
                uint32_t e0 = aw[7], e1 = xw[7];
#pragma unroll
                for (int k = 6; k >= 0; k--)
                    if (ovf & (1u << k)) { e0 = aw[k]; e1 = xw[k]; }
                const uint32_t pos = ovf ? (wpos & 31) + __popc(bal & ltmask) : 64, next = wpos + __popc(bal);
                asm volatile("{.reg .pred p; setp.lt.u32 p,%3,32; @p st.shared.v2.u32 [%0],{%1,%2};}" ::"r"(stage + pos * 8), "r"(e0), "r"(e1), "r"(pos) : "memory");
                if ((next ^ wpos) & 32) {
                    flush_stage();
                    asm volatile("{.reg .pred p; setp.lt.u32 p,%3,32; @p st.shared.v2.u32 [%0],{%1,%2};}" ::"r"(stage + (pos - 32) * 8), "r"(e0), "r"(e1), "r"(pos - 32) : "memory");
                }
                wpos = next;
                ovf &= ovf - 1;
                bal = __ballot_sync(0xffffffffu, ovf != 0);
            }
            if (R) load_log((k2 - np) * 2 + G + 1);
            if (G || !R || k2 != np + NR / 2 - 1) {
                if (G != sw) { cur1 = nxt1 + C * 2; nxt1 = fresh - XG; } else { cur0 = nxt0 + C * 2; nxt0 = fresh; }
            }
            fresh += fresh == xk + (NP - 1) * XG - C * 2 ? -(NP - 1) * XG : XG;
        };
        for (int stop = snap; h_in < total;) {
            load_in(0); load_in(1);
            while (true) {
                step(np, Kind<false, 0>());
                step(np, Kind<false, 1>());
                np++;
                if (h_in < stop && wpos <= LOGCAP - 512) continue;
                if (h_in >= stop && stop < total) {
                    const uint32_t nch = min(wpos / 32, (LOGCAP - 256 * NR) / 32);
                    uint32_t base = 0;
                    if (lane == 0) base = (uint32_t)atomicAdd(logsync, (u64)nch);
                    base = __shfl_sync(0xffffffffu, base, 0);
                    const uint32_t mine = min(nch, NCH - min(base, NCH));
                    for (uint32_t c = lane; c < mine; c += 32) g_chunks[base + c] = (pid * NW + warp) * (LOGCAP / 32) + c + 1;
                    n0 = mine * 32;
                    __syncwarp();
                    if (n0 && elect_one()) asm volatile("cp.async.bulk.prefetch.L2.global [%0],%1;" ::"l"(log), "r"(n0 * 8) : "memory");
                    __syncwarp();
                    bar_arrive(BAR_LOG, (NW + 1) * 32);
                    stop = total;
                }
                if (h_in >= total || wpos > LOGCAP - 512) break;
            }
            if (wpos > LOGCAP - 512) drain();
        }
        {
            u64 v; int spins = 0;
            do {
                asm volatile("ld.acquire.gpu.global.u64 %0,[%1];" : "=l"(v) : "l"(logsync) : "memory");
                if (++spins > (1 << 22)) __trap();
            } while ((v >> 32) < N1);
            const uint32_t idx = (((lane / NR) * NW + warp) * NR + lane % NR) * N1 + pid;
            if (lane < 8 * NR && idx < (uint32_t)v) chunk = __ldcg(g_chunks + idx);
            __syncwarp();
        }
        if (wpos > LOGCAP - 256 * NR) drain();
        load_log(0);
#pragma unroll 1
        for (int k2 = np; k2 < np + NR / 2; k2++) {
            step(k2, Kind<true, 0>());
            step(k2, Kind<true, 1>());
        }
        uint2* const rng = (uint2*)(sm + SM_S1_END);
        if (lane == 0) rng[warp] = make_uint2(n0, wpos);
        if (wpos & 31) flush_stage();
        __syncwarp();
        for (int g = 0; g < NG; g++) {
            mbar_wait(mb + g * 8, (np + NR / 2) & 1);
            mbar_wait(mb + 16 + g * 8, (np + NR / 2) & 1);
            bar_arrive(BAR_ATOMS, NT_ATOMS);
            bar_arrive(BAR_STS + g, NT_STS);
        }
        const uint2 mine = lane < NW ? rng[lane] : make_uint2(0, 0);
        const uint32_t nch = (mine.y - mine.x + 31) / 32;
        uint32_t end = nch;
#pragma unroll
        for (int d = 1; d < 32; d *= 2) {
            const uint32_t t = __shfl_up_sync(0xffffffffu, end, d);
            if (lane >= d) end += t;
        }
        direct(warp, NW, __shfl_sync(0xffffffffu, end, 31), [&](uint32_t c, uint32_t& lo, uint32_t& hi) {
            const int w = __popc(__ballot_sync(0xffffffffu, end <= c));
            const uint32_t lb = (pid * NW + w) * LOGCAP;
            lo = lb + __shfl_sync(0xffffffffu, mine.x + (c - (end - nch)) * 32, w);
            hi = lb + __shfl_sync(0xffffffffu, mine.y, w);
        }, [&] { bar_sync(BAR_W, (NW + 1) * 32); });
    } else if (warp == NW) {
        const int row = min(lane, NO - 1), swz = (row >> 1) & 3;
        mbar_arrive(mb);
        int pn = N1 + pid, pnn = 0, nc = 0x7ffffff0;
        for (int s = 0; s < nc; s++) {
            const int hn = min(pn * 2 + (s & 1), total);
            if (hn == total) nc = min(nc, s + 2 + NR + 2);
            const uint32_t sub = s == nc - 4 ? 0 : C, bias = s == nc - 2 ? C : 0;
            uint4* cp = (uint4*)(sm + SM_CNT + ((s ^ sw) & 1) * GB * 4) + row * 4;
            bar_sync(BAR_ATOMS, NT_ATOMS);
            uint4 c[4];
#pragma unroll
            for (int j = 0; j < 4; j++) c[j] = cp[j ^ swz];
            __syncwarp();
#pragma unroll
            for (int j = 0; j < 4; j++)
                cp[j ^ swz] = make_uint4(min(max(c[j].x, C), 2 * C) - sub, min(max(c[j].y, C), 2 * C) - sub,
                                         min(max(c[j].z, C), 2 * C) - sub, min(max(c[j].w, C), 2 * C) - sub);
            if (lane == 0 && !(s & 1)) {
                s_next[0] = hn; s_next[2] = nc;
                if (hn >= snap) s_next[3] = min(s_next[3], s + 1);
            }
            mbar_arrive(mb + ((s + 1) & 1) * 8);
            uint4 w = make_uint4(0, 0, 0, 0);
#pragma unroll
            for (int j = 0; j < 4; j++) {
                const int sh = (j ^ swz) * 8;
                w.x |= min(c[j].x - bias, C) << sh; w.y |= min(c[j].y - bias, C) << sh;
                w.z |= min(c[j].z - bias, C) << sh; w.w |= min(c[j].w - bias, C) << sh;
            }
            mbar_wait(mb + 16 + (s & 1) * 8, (s >> 1) & 1);
            ((uint4*)(sm + SM_CB + (s & 1) * GB))[row] = w;
            bar_arrive(BAR_STS + (s & 1), NT_STS);
            if (s & 1) pn = min(2 * N1 + __shfl_sync(0xffffffffu, pnn, 0), p.pairs);
            else if (hn < total && s / 2 + 2 < KMAX) {
                if (lane == 0) asm volatile("atom.relaxed.gpu.global.add.u32 %0,[%1],1;" : "=r"(pnn) : "l"(&g_sync[SY_WORK]) : "memory");
            } else pnn = p.pairs;
            const int hp = pn * 2 + ((s & 1) ^ 1);
            if (hp < total && elect_one())
                asm volatile("cp.async.bulk.prefetch.L2.global [%0],%1;" ::"l"(p.angle + hp * STEP), "r"(STEP * 2) : "memory");
            __syncwarp();
        }
    } else if (warp < NW + 3) {
        const int par = warp - NW - 1, g = par ^ sw;
        mbar_arrive(mb + 16 + par * 8);
        const uint32_t* const fb = flags() + flag_idx(sm, g, lane & 1, pid);
        for (int s = par; s < s_next[2]; s += 2) {
            const int k = s >> 1, slot = k % DA * N1 + pid, slots = k % DS * N1 + pid, pl = s % NP;
            const uint32_t cls = __shfl_sync(0xffffffffu, cls_of(sm, slot, g), 0), clss = __shfl_sync(0xffffffffu, cls_of(sm, slots, g), 0);
            if (k >= DS) {
                const uint32_t kw = k - ((lane & 1) ? DS : DA - DV);
                wait_flag(fb + (kw & 1), arrivals(lane & 1, kw));
                __syncwarp();
                asm volatile("fence.proxy.async.global;" ::: "memory");
            }
            bar_sync(BAR_STS + par, NT_STS);
            asm volatile("fence.proxy.async.shared::cta;" ::: "memory");
            if (elect_one()) {
                unsigned char* dst = g_ring + slot_a(slot);
#pragma unroll
                for (int j = 0; j < IG / 2; j++)
                    asm volatile("cp.async.bulk.global.shared::cta.bulk_group [%0],[%1],%2;" ::"l"(g_ring + slot_a(slots) + ring_off(clss, j * 4096)),
                                 "r"(sb + SM_A + pl * AG + j * 2 * ASEG), "n"(2 * ASEG) : "memory");
#pragma unroll
                for (int j = 0; j * 4096 < XG; j++)
                    asm volatile("cp.async.bulk.global.shared::cta.bulk_group [%0],[%1],%2;" ::"l"(dst + ring_off(cls, XO + j * 4096)),
                                 "r"(sb + SM_X + pl * XG + j * 4096), "r"(min(4096, XG - j * 4096)) : "memory");
                asm volatile("cp.async.bulk.global.shared::cta.bulk_group [%0],[%1],%2;" ::"l"(dst + ring_off(cls, XO + XG)),
                             "r"(sb + SM_CB + par * GB), "r"(GB) : "memory");
                asm volatile("cp.async.bulk.commit_group;" ::: "memory");
                asm volatile("cp.async.bulk.wait_group 0;" ::: "memory");
            }
            __syncwarp();
            mbar_arrive(mb + 16 + par * 8);
            bar_sync(BAR_PUBFREE + par, 64);
            bar_arrive(BAR_PUB + par, 64);
        }
    } else if (warp == NW + 3) {
        uint32_t* const fb = flags() + flag_idx(sm, (lane >> 1) & 1, lane & 1, pid);
        bar_arrive(BAR_PUBFREE, 64);
        bar_arrive(BAR_PUBFREE + 1, 64);
        for (int s = 0; s < s_next[2]; s++) {
            if (s == 4) { wait_zeroed(); __syncwarp(); }
            const int g = (s ^ sw) & 1;
            bar_sync(BAR_PUB + (s & 1), 64);
            if (s + 2 < s_next[2]) bar_arrive(BAR_PUBFREE + (s & 1), 64);
            const bool pooled = s == s_next[3];
            if (pooled) bar_sync(BAR_LOG, (NW + 1) * 32);
            asm volatile("fence.release.gpu;" ::: "memory");
            if ((lane >> 1) == g) asm volatile("red.relaxed.gpu.global.add.u32 [%0],%1;" ::"l"(fb + ((s >> 1) & 1)), "r"(FL_DATA) : "memory");
            if (pooled && lane == 0) asm volatile("red.relaxed.gpu.global.add.u64 [%0],%1;" ::"l"(logsync), "l"(1ull << 32) : "memory");
            __syncwarp();
        }
        bar_arrive(BAR_W, (NW + 1) * 32);
    }
}

__device__ __forceinline__ void stage2(const Params& p, unsigned char* sm, int g, int ig) {
    const int warp = warp_id(), lane = lane_id();
    constexpr uint32_t sb = SB;
    constexpr int NCW = 16, STEPS = NO / 4, TAB = NCW * ASEG, MB = TAB + SI * 8;
    static_assert(MB + 8 * NCW + 8 <= SM_AUX && MB % 8 == 0, "stage2 smem");
    if (threadIdx.x <= NCW) asm volatile("mbarrier.init.shared::cta.b64 [%0],1;" ::"r"(sb + MB + threadIdx.x * 8) : "memory");
    asm volatile("fence.proxy.async.shared::cta;" ::: "memory");
    __syncthreads();
    if (warp == 30) {
        const int e0 = (g * IG + ig) * SI, bytes = max(0, min((int)SI, p.E - e0)) * 8;
        if (elect_one()) {
            asm volatile("mbarrier.arrive.expect_tx.shared::cta.b64 _,[%0],%1;" ::"r"(sb + MB + NCW * 8), "r"(bytes) : "memory");
            for (int o = 0; o < bytes; o += 16384)
                asm volatile("cp.async.bulk.shared::cluster.global.mbarrier::complete_tx::bytes [%0],[%1],%2,[%3];" ::"r"(sb + TAB + o), "l"((const char*)(p.m + e0) + o), "r"(min(16384, bytes - o)), "r"(sb + MB + NCW * 8) : "memory");
        }
        __syncwarp();
    }
    if (warp == 31) poller<NCW, FL_GO2>(sm, g, ig >> 1, 0, p.units, p.units - 3 * N1, [&] {
            const int e0 = (g * IG + ig) * SI, n = min((int)SI, p.E - e0);
            if (n > 0 && elect_one()) asm volatile("cp.async.bulk.prefetch.L2.global [%0],%1;" ::"l"(p.m + e0), "r"(n * 8) : "memory");
            __syncwarp();
        });
    if (warp >= NCW) return;
    const uint32_t f2 = (uint32_t)p.freq[0] * 0x10001u;
    const uint32_t vlane = slot_v(0) + (lane >> 4) * 8192 + ((lane >> 3) & 1) * VSEG + ig * 128 + (lane & 7) * 16;
    const uint32_t aoff = (ig >> 1) * 8192 + (ig & 1) * ASEG, buf = sb + warp * ASEG, mb = sb + MB + warp * 8;
    auto fetch = [&](uint32_t e) {
        if (elect_one()) {
            asm volatile("mbarrier.arrive.expect_tx.shared::cta.b64 _,[%0],%1;" ::"r"(mb), "n"(ASEG) : "memory");
            asm volatile("cp.async.bulk.shared::cluster.global.mbarrier::complete_tx::bytes [%0],[%1],%2,[%3];" ::"r"(buf),
                         "l"(g_ring + (slot_a((e >> 16) & 0xff) + aoff + ((e >> 2) & 0x1000))), "n"(ASEG), "r"(mb) : "memory");
        }
        __syncwarp();
    };
    mbar_wait(sb + MB + NCW * 8, 0);
    uint2 qn = make_uint2(0, 0);
    bool have = false;
    uint32_t ph = 0;
    for (int t = warp; t < p.units; t += NCW) {
        if (!have) { next_unit<true>(sb + SM_AUX, warp, t, NCW, qn); fetch(qn.x); }
        const uint2 qe = qn;
        mbar_wait(mb, ph); ph ^= 1;
        uint2 a[STEPS];
#pragma unroll
        for (int j = 0; j < STEPS; j++) asm volatile("ld.shared.v2.u32 {%0,%1},[%2];" : "=r"(a[j].x), "=r"(a[j].y) : "r"(buf + j * 256 + lane * 8) : "memory");
        have = next_unit<false>(sb + SM_AUX, warp, t + NCW, NCW, qn);
        uint32_t big = 0, x2[STEPS];
#pragma unroll
        for (int j = 0; j < STEPS; j++) {
            x2[j] = hmul2(__byte_perm(a[j].x, a[j].y, 0x7632), f2);
            a[j].x = __byte_perm(a[j].x, a[j].y, 0x5410);
            big |= (x2[j] & 0x7fff7fffu) + 0x3e003e00u;
        }
        const bool slow = __any_sync(0xffffffffu, big & 0x80008000u);
        if (have) fetch(qn.x + ((uint32_t)slow & p.zero));
        if (slow) {
#pragma unroll
            for (int j = 0; j < STEPS; j++) x2[j] = pack2(cos_slow(bf_lo(x2[j])), cos_slow(bf_hi(x2[j])));
        }
        const uint32_t tag = qe.x >> 31, cq = (qe.x >> (lane >> 4)) << 12;
        const uint32_t vo = ((qe.x >> 24) & 0x7f) * (PV * 8192) + vlane;
        uint2 m0[STEPS], m1[STEPS];
#pragma unroll
        for (int jj = 0; jj < STEPS + 1; jj++) {
            if (jj < STEPS) {
                asm volatile("ld.shared.v2.u32 {%0,%1},[%2];" : "=r"(m0[jj].x), "=r"(m0[jj].y) : "r"(sb + TAB + (a[jj].x & 0xffff) * 8) : "memory");
                asm volatile("ld.shared.v2.u32 {%0,%1},[%2];" : "=r"(m1[jj].x), "=r"(m1[jj].y) : "r"(sb + TAB + (a[jj].x >> 16) * 8) : "memory");
            }
            if (jj >= 1) {
                const int j = jj - 1;
                const uint32_t cf = pack2(__cosf(bf_lo(x2[j])), __cosf(bf_hi(x2[j]))), c2 = slow ? x2[j] : cf;
                const uint32_t d0 = __byte_perm(c2, 0, 0x1010), d1 = __byte_perm(c2, 0, 0x3232);
                st128(g_ring + (vo | ((cq >> (2 * j)) & 0x1000)) + j * 16384,
                      make_uint4((hmul2(m0[j].x, d0) & ~1u) | tag, hmul2(m0[j].y, d0), hmul2(m1[j].x, d1), hmul2(m1[j].y, d1)));
                if (p.zero) __nanosleep(0);
            }
        }
        __syncwarp();
        if (qe.y & 0x8000) asm volatile("fence.acq_rel.gpu;" ::: "memory");
        if (lane == 0) asm volatile("red.relaxed.gpu.global.add.u32 [%0],1;" ::"l"(flags() + (qe.y & 0x7fff)) : "memory");
    }
}

constexpr int EXPORT_LO = 20, EXPORT_N = 31 - EXPORT_LO;
__device__ __forceinline__ uint2 lock64(uint32_t a) {
    uint2 r;
    asm volatile("{.reg .b64 y; atom.shared.exch.b64 y,[%2],0xffffffffffffffff; mov.b64 {%0,%1},y;}" : "=r"(r.x), "=r"(r.y) : "r"(a) : "memory");
    return r;
}

__device__ __forceinline__ void stage3(const Params& p, unsigned char* sm, int g, int o) {
    const int warp = warp_id(), lane = lane_id();
    constexpr uint32_t sb = SB;
    if (threadIdx.x < 64) ((uint32_t*)(sm + SM_AUX + AUX_DUMMY))[threadIdx.x] = ~0u;
    for (int i = (g * NO + o) * 1024 + threadIdx.x; i < NO * (int)SO / 2; i += N3 * 1024) ((uint4*)g_agg)[i] = make_uint4(0, 0, 0, 0);
    __syncthreads();
    if (threadIdx.x == 0) asm volatile("red.release.gpu.global.add.u32 [%0],1;" ::"l"(&g_sync[SY_ZERO]) : "memory");
    const int t0 = p.pairs * 2 * STEP + (g * NO + o) * 1024 + threadIdx.x;
    static_assert(2 * STEP <= N3 * 1024, "remainder");
    if (t0 - lane < p.T) {
        const int t = min(t0, p.T - 1);
        const uint2 v = __ldg(p.m + p.idx_in[t]);
        wait_zeroed();
        if (t0 < p.T) red_agg(p.idx_out[t], v, dup_bf16(cos_any(rbf16(bf_lo(p.freq[0]) * bf_lo(p.angle[t])))));
        __syncwarp();
    }
    constexpr int NCW = 20, STEPS = IG / 4;
    if (warp == 31) {
        poller<NCW, FL_GO3>(sm, g, (XO + o * XSEG) >> 12, (XO + XG) >> 12, p.units, p.units - 2 * N1, [&] {
            constexpr int H = (SO / 2 + 7) & ~7;
            const int e0 = (o * SO + g * H) & ~7, n = min(H + 8, p.E - e0) & ~7;
            if (n > 0 && elect_one()) {
                asm volatile("cp.async.bulk.prefetch.L2.global [%0],%1;" ::"l"(g_agg + e0), "r"(n * 8) : "memory");
                asm volatile("cp.async.bulk.prefetch.L2.global [%0],%1;" ::"l"(p.dist + e0), "r"(n * 2) : "memory");
            }
            __syncwarp();
        });
    } else if (warp < NCW) {
        const uint32_t dummy = sb + SM_AUX + AUX_DUMMY + lane * 8, r0 = (lane & 7) * 2;
        const uint32_t vlane = slot_v(0) + ring_off(0, o * VSEG) + lane * 16, xlane = ring_off(0, XO + o * XSEG) + lane * 4;
        const uint32_t clane = ring_off(0, XO + XG + o * IG) + (lane >> 3) * 4;
        for (int t = warp; t < p.units; t += NCW) {
            uint2 qe;
            next_unit<true>(sb + SM_AUX, warp, t, NCW, qe);
            const uint32_t tag = qe.x >> 31, ab = slot_a((qe.x >> 16) & 0xff);
            const uint4* vp = (const uint4*)(g_ring + (((qe.x >> 24) & 0x7f) * (PV * 8192) + vlane + (((qe.x >> (o >> 1)) & 1) << 12)));
            const uint32_t* xp = (const uint32_t*)(g_ring + (ab + xlane + ((qe.x >> 2) & 0x1000)));
            const uint32_t* cp = (const uint32_t*)(g_ring + (ab + clane + ((qe.x >> 3) & 0x1000)));
            uint4 v[STEPS]; uint32_t x[STEPS];
            const uint32_t cn = __ldcg(cp);
#pragma unroll
            for (int j = 0; j < STEPS; j++) x[j] = __ldcg(xp + j * 32);
#pragma unroll
            for (int j = 0; j < STEPS; j++) v[j] = ld128(vp + j * 32);
            for (int spins = 0;; spins++) {
                uint32_t bad = 0;
#pragma unroll
                for (int j = 0; j < STEPS; j++) bad |= v[j].x ^ tag;
                if (!__any_sync(0xffffffffu, bad & 1)) break;
                if (spins > (1 << 22)) __trap();
#pragma unroll
                for (int j = 0; j < STEPS; j++) v[j] = ld128(vp + j * 32);
            }
            uint32_t ad[2 * STEPS], dep = cn;
#pragma unroll
            for (int j = 0; j < STEPS; j++) {
                const uint32_t c = (cn >> (8 * j)) & 0xff;
                ad[2 * j] = r0 < c ? sb + (x[j] & 0xffff) * 8 : dummy;
                ad[2 * j + 1] = r0 + 1 < c ? sb + (x[j] >> 16) * 8 : dummy;
                dep ^= x[j];
            }
            if (lane == 0) asm volatile("red.relaxed.gpu.global.add.u32 [%0],%1;" ::"l"(flags() + (qe.y & 0x7fff)), "r"(1 + (dep & p.zero)) : "memory");
            uint32_t pend = 0;
#pragma unroll
            for (int j0 = 0; j0 < 2 * STEPS; j0 += 4) {
                uint2 t[4];
#pragma unroll
                for (int j = 0; j < 4; j++) t[j] = lock64(ad[j0 + j]);
#pragma unroll
                for (int j = 0; j < 4; j++) {
                    const int jj = j0 + j;
                    const uint32_t vx = (jj & 1) ? v[jj / 2].z : v[jj / 2].x, vy = (jj & 1) ? v[jj / 2].w : v[jj / 2].y;
                    asm volatile("{.reg .pred p,q; setp.ne.u32 p,%4,0xffffffff; @p st.shared.v2.u32 [%1],{%2,%3}; setp.ne.and.u32 q,%1,%5,!p; @q or.b32 %0,%0,%6;}"
                                 : "+r"(pend) : "r"(ad[jj]), "r"(hadd2(t[j].x, vx)), "r"(hadd2(t[j].y, vy)), "r"(t[j].x), "r"(dummy), "r"(1u << jj) : "memory");
                }
            }
            while (__any_sync(0xffffffffu, pend)) {
                uint32_t a = dummy, vx = 0, vy = 0;
#pragma unroll
                for (int jj = 2 * STEPS - 1; jj >= 0; jj--)
                    if (pend & (1u << jj)) { a = ad[jj]; vx = (jj & 1) ? v[jj / 2].z : v[jj / 2].x; vy = (jj & 1) ? v[jj / 2].w : v[jj / 2].y; }
                const uint2 t = lock64(a);
                asm volatile("{.reg .pred p; setp.ne.u32 p,%4,0xffffffff; @p st.shared.v2.u32 [%1],{%2,%3}; @p and.b32 %0,%0,%5;}"
                             : "+r"(pend) : "r"(a), "r"(hadd2(t.x, vx)), "r"(hadd2(t.y, vy)), "r"(t.x), "r"(pend - 1) : "memory");
            }
        }
    }
    if (warp < NCW) bar_arrive(1, 992);
}

__device__ __forceinline__ void mma_edge(float (&c)[4], uint32_t p01, uint32_t q01, uint32_t p23, uint32_t q23, uint2 b) {
    asm("mma.sync.aligned.m16n8k16.row.col.f32.bf16.bf16.f32 {%0,%1,%2,%3},{%4,%5,%6,%7},{%8,%9},{%0,%1,%2,%3};"
        : "+f"(c[0]), "+f"(c[1]), "+f"(c[2]), "+f"(c[3]) : "r"(p01), "r"(q01), "r"(p23), "r"(q23), "r"(b.x), "r"(b.y));
}
__device__ __forceinline__ uint2 b_frag(const uint16_t* w, int j0) {
    int lane; asm("mov.u32 %0,%%laneid;" : "=r"(lane));
    const int j = j0 + ((lane >> 2) & 1);
    const uint2 v = make_uint2(w[j] | ((uint32_t)w[4 + j] << 16), w[8 + j] | ((uint32_t)w[12 + j] << 16));
    return (lane & 3) == (lane >> 3) ? v : make_uint2(0, 0);
}
__device__ __forceinline__ void edge_gates(const uint16_t* w, uint32_t d2, uint4& sp, uint4& gp) {
    uint32_t rb[2][4];
#pragma unroll
    for (int k = 0; k < 2; k++)
#pragma unroll
        for (int r = 0; r < 4; r++) {
            uint32_t x; asm("sub.rn.bf16x2 %0,%1,%2;" : "=r"(x) : "r"(__byte_perm(d2, 0, k ? 0x3232 : 0x1010)), "r"(((const uint32_t*)w)[48 + r]));
            const uint32_t t = hmul2(hmul2(x, x), 0xc120c120u);
            rb[k][r] = pack2(__expf(bf_lo(t)), __expf(bf_hi(t)));
        }
    uint32_t o[4][2];
#pragma unroll
    for (int n = 0; n < 4; n++) {
        float c[4] = {};
        mma_edge(c, rb[0][0], rb[1][0], rb[0][1], rb[1][1], b_frag(w + (n >> 1) * 32, (n & 1) * 2));
        mma_edge(c, rb[0][2], rb[1][2], rb[0][3], rb[1][3], b_frag(w + (n >> 1) * 32 + 16, (n & 1) * 2));
        o[n][0] = pack2(c[0], c[1]); o[n][1] = pack2(c[2], c[3]);
    }
    gp = make_uint4(o[0][0], o[1][0], o[0][1], o[1][1]);
    sp = make_uint4(o[2][0], o[3][0], o[2][1], o[3][1]);
}
__device__ __forceinline__ uint4 edge_finish(const uint16_t* w, uint4 a, uint4 sp, uint4 gp, uint4 mv) {
    float t0[4] = {}, t1[4] = {}, u0[4] = {}, u1[4] = {};
    mma_edge(t0, a.x, a.z, a.y, a.w, b_frag(w + 64, 0));
    mma_edge(t1, a.x, a.z, a.y, a.w, b_frag(w + 64, 2));
    const uint32_t p01 = pack2(t0[0] * bf_lo(sp.x), t0[1] * bf_hi(sp.x)), p23 = pack2(t1[0] * bf_lo(sp.y), t1[1] * bf_hi(sp.y));
    const uint32_t q01 = pack2(t0[2] * bf_lo(sp.z), t0[3] * bf_hi(sp.z)), q23 = pack2(t1[2] * bf_lo(sp.w), t1[3] * bf_hi(sp.w));
    mma_edge(u0, p01, q01, p23, q23, b_frag(w + 80, 0));
    mma_edge(u1, p01, q01, p23, q23, b_frag(w + 80, 2));
    return make_uint4(hadd2(mv.x, hmul2(pack2(u0[0], u0[1]), gp.x)), hadd2(mv.y, hmul2(pack2(u1[0], u1[1]), gp.y)),
                      hadd2(mv.z, hmul2(pack2(u0[2], u0[3]), gp.z)), hadd2(mv.w, hmul2(pack2(u1[2], u1[3]), gp.w)));
}

__device__ __forceinline__ void finish(const Params& p, unsigned char* sm) {
    __syncwarp();
    const int b = blockIdx.x, tid = threadIdx.x;
    const int role = ((const volatile uint32_t*)(sm + SM_AUX + AUX_MISC))[2];
    const uint16_t* w = (const uint16_t*)(sm + SM_AUX + AUX_W);
    if (role != 3) {
        __syncthreads();
        if (tid == 0) asm volatile("red.release.gpu.global.add.u32 [%0],1;" ::"l"(&g_sync[SY_END]) : "memory");
    }
    constexpr int EP = 3, es = NCTA * 1024;
    static_assert(EP * es * 2 >= E_CAP, "epilogue");
    uint4 sg[2 * EP];
    const int e0 = b * 1024 + tid, np = p.E / 2;
#pragma unroll
    for (int k = 0; k < EP; k++) sg[2 * k].x = __ldg((const uint32_t*)p.dist + min(e0 + k * es, np - 1));
#pragma unroll
    for (int k = 0; k < EP; k++) edge_gates(w, sg[2 * k].x, sg[2 * k], sg[2 * k + 1]);
    uint4 mv[EP];
#pragma unroll
    for (int k = 0; k < EP; k++) mv[k] = __ldg((const uint4*)p.m + min(e0 + k * es, np - 1));
    if (role == 3) {
        const int et = tid - EXPORT_LO * 32;
        if (et >= 0 && et < EXPORT_N * 32) {
            const int q0 = (((const volatile uint32_t*)(sm + SM_AUX + AUX_MISC))[3] & 255) * (SO / 2);
            wait_zeroed();
            __syncwarp();
            bar_sync(1, 992);
#pragma unroll 4
            for (int i = et - (q0 & 7); i < (int)SO / 2; i += EXPORT_N * 32) {
                if (i < 0) continue;
                const uint4 v = ((const uint4*)sm)[i];
                asm volatile("red.global.add.noftz.v4.bf16x2 [%0],{%1,%2,%3,%4};" ::"l"((uint4*)g_agg + q0 + i), "r"(v.x), "r"(v.y), "r"(v.z), "r"(v.w) : "memory");
            }
            __syncwarp();
            bar_arrive(2, 1024);
            bar_sync(3, EXPORT_N * 32);
            if (et == 0) asm volatile("red.release.gpu.global.add.u32 [%0],1;" ::"l"(&g_sync[SY_END]) : "memory");
            __syncwarp();
        } else bar_sync(2, 1024);
    }
    uint4* const stash = (uint4*)sm + tid;
#pragma unroll
    for (int k = 0; k < EP; k++) { stash[(3 * k) * 1024] = sg[2 * k]; stash[(3 * k + 1) * 1024] = sg[2 * k + 1]; stash[(3 * k + 2) * 1024] = mv[k]; }
    if (tid == 0) {
        wait_flag(&g_sync[SY_END], NCTA);
        asm volatile("fence.acquire.gpu;" ::: "memory");
    }
    __syncthreads();
    uint4 av[EP];
#pragma unroll
    for (int k = 0; k < EP; k++) av[k] = __ldcg((const uint4*)g_agg + min(e0 + k * es, np - 1));
#pragma unroll
    for (int k = 0; k < EP; k++) {
        const uint4 o = edge_finish(w, av[k], stash[(3 * k) * 1024], stash[(3 * k + 1) * 1024], stash[(3 * k + 2) * 1024]);
        if (e0 + k * es < np) ((uint4*)p.out)[e0 + k * es] = o;
    }
    if (b == 0 && tid < 512) ((uint4*)flags())[tid] = make_uint4(0, 0, 0, 0);
    if (tid == 0) {
        g_info[b] = make_uint2(0, 0);
        if (atomicAdd(&g_sync[SY_EXIT], 1) == NCTA - 1)
            g_sync[SY_ZERO] = g_sync[SY_END] = g_sync[SY_EXIT] = g_sync[SY_WORK] = g_sync[SY_LOG] = g_sync[SY_LOG + 1] = 0;
    }
}

__global__ void __launch_bounds__(1024, 1) main_kernel(const __grid_constant__ Params p) {
    extern __shared__ __align__(128) unsigned char sm[];
    const int b = blockIdx.x, tid = threadIdx.x, warp = tid >> 5;
    if ((uint32_t)__cvta_generic_to_shared(sm) != SB) __trap();
    uint32_t* s_misc = (uint32_t*)(sm + SM_AUX + AUX_MISC);
    if (tid == 0) s_misc[0] = s_misc[4] = s_misc[5] = 0;
    __syncthreads();
    if ((tid & 31) == 0) {
        const int sl = b * 2 + (warp >> 4), j = warp & 15;
        if (warp == 31) s_misc[1] = upper_is_near(g_probe + (b & 127) * 32);
        else if (sl < NSL && j < (sl < KA ? PA : sl < KA + KV ? PV : 1) &&
                 upper_is_near(g_ring + (sl < KA ? slot_a(sl) : slot_v(sl - KA)) + j * 8192 + 4064))
            atomicOr(&s_misc[0], 1u << warp);
    }
    __syncwarp();
    __syncthreads();
    uint32_t me; asm("mov.u32 %0,%%smid;" : "=r"(me));
    me = 0x8000u | (s_misc[1] << 14) | (me & 0x3fff);
    if (tid == 0) {
        const u64 v = (u64)(s_misc[0] ^ (s_misc[1] ? ~0u : 0u)) | ((u64)me << 32);
        asm volatile("st.release.gpu.global.u64 [%0],%1;" ::"l"(&g_info[b]), "l"(v) : "memory");
    }
    for (int i = tid; i < (SM_AUX + AUX_CLS) / 16; i += 1024) ((uint4*)sm)[i] = make_uint4(0, 0, 0, 0);
    uint16_t* w = (uint16_t*)(sm + SM_AUX + AUX_W);
    if (tid < 160) {
        u64 v = 0; int spins = 0;
        while (tid < NCTA && !(v >> 32)) {
            asm volatile("ld.acquire.gpu.global.u64 %0,[%1];" : "=l"(v) : "l"(&g_info[tid]) : "memory");
            if (++spins > (1 << 22)) __trap();
        }
        __syncwarp();
        if (tid < NCTA) ((uint32_t*)(sm + SM_AUX + AUX_CLS))[tid] = (uint32_t)v;
        const uint32_t o = v >> 32;
        const uint32_t c = __reduce_add_sync(0xffffffffu, tid < NCTA ? 1u << (8 * ((o & 1) | ((o >> 13) & 2))) : 0u);
        const uint32_t r = __popc(__ballot_sync(0xffffffffu, tid < NCTA && ((o ^ me) & 0x4001) == 0 && (o > me || (o == me && tid > b))));
        if ((tid & 31) == 0) { atomicAdd(&s_misc[4], c); atomicAdd(&s_misc[5], r); }
    } else if (tid >= 256 && tid < 256 + 104) {
        const int j = tid - 256;
        w[j] = j < 32 ? p.w_rbf[j] : j < 64 ? p.w_sbf[j - 32] : j < 80 ? p.w_down[j - 64] : j < 96 ? p.w_up[j - 80] : p.centers[j - 96];
    }
    __syncthreads();
    int role, rank;
    {
        const uint32_t cnt = s_misc[4], cl = (me & 1) | ((me >> 13) & 2);
        rank = s_misc[5];
        const int c2 = (rank + 1) * IG / NO;
        if (__vminu4(cnt, NO * 0x01010101u) != NO * 0x01010101u) {
            role = b < N2 ? 2 : b < N2 + N3 ? 3 : 1;
            const int r = role == 2 ? b : b - N2;
            rank = role == 1 ? b - N2 - N3 : (r >> 1) | ((r & 1) << 8);
        } else if (rank < NO && (me & 1)) { role = 3; rank |= (cl >> 1) << 8; }
        else if (rank < NO && c2 != rank * IG / NO) { role = 2; rank = (c2 - 1) | ((cl >> 1) << 8); }
        else {
            role = 1;
            rank -= (me & 1) ? NO : min(c2, IG);
            for (uint32_t c = 0; c < cl; c++) rank += ((cnt >> (8 * c)) & 0xff) - ((c & 1) ? NO : IG);
        }
        if (tid == 0) { s_misc[2] = role; s_misc[3] = rank; }
    }
    if (role == 1) stage1(p, sm, rank);
    else if (role == 2) stage2(p, sm, rank >> 8, rank & 255);
    else stage3(p, sm, rank >> 8, rank & 255);
    finish(p, sm);
}

__global__ void generic_scatter(const __grid_constant__ Params p) {
    const float f = bf_lo(p.freq[0]);
    for (int t = blockIdx.x * blockDim.x + threadIdx.x; t < p.T; t += gridDim.x * blockDim.x) {
        const uint2 v = __ldg(p.m + p.idx_in[t]);
        const uint32_t c2 = dup_bf16(cos_any(rbf16(f * bf_lo(p.angle[t]))));
        asm volatile("red.global.add.noftz.v2.bf16x2 [%0],{%1,%2};" ::"l"(p.out + p.idx_out[t]), "r"(hmul2(v.x, c2)), "r"(hmul2(v.y, c2)) : "memory");
    }
}
__global__ void __launch_bounds__(256) generic_finish(const __grid_constant__ Params p) {
    __shared__ __align__(16) uint16_t w[104];
    const int j = threadIdx.x, e = blockIdx.x * blockDim.x + j, ec = min(e, p.E - 1);
    if (j < 104) w[j] = j < 32 ? p.w_rbf[j] : j < 64 ? p.w_sbf[j - 32] : j < 80 ? p.w_down[j - 64] : j < 96 ? p.w_up[j - 80] : p.centers[j - 96];
    const uint2 a = p.out[ec], mv = p.m[ec];
    __syncthreads();
    uint4 s0, s1;
    edge_gates(w, p.dist[ec] * 0x10001u, s0, s1);
    const uint4 o = edge_finish(w, make_uint4(a.x, a.y, a.x, a.y), s0, s1, make_uint4(mv.x, mv.y, mv.x, mv.y));
    if (e < p.E) p.out[e] = make_uint2(o.x, o.y);
}

extern "C" void kernel_launch(void* const* d_in, const int* in_sizes, int n_in, void* d_out, int out_size) {
    static int nsm = 0;
    if (!nsm) {
        cudaDeviceGetAttribute(&nsm, cudaDevAttrMultiProcessorCount, 0);
        cudaFuncSetAttribute(main_kernel, cudaFuncAttributeMaxDynamicSharedMemorySize, SMEM_BYTES);
    }
    Params p;
    p.m = (const uint2*)d_in[0]; p.idx_in = (const int*)d_in[1]; p.idx_out = (const int*)d_in[2];
    p.angle = (const uint16_t*)d_in[4]; p.freq = (const uint16_t*)d_in[6];
    p.dist = (const uint16_t*)d_in[3]; p.centers = (const uint16_t*)d_in[5]; p.w_rbf = (const uint16_t*)d_in[7];
    p.w_sbf = (const uint16_t*)d_in[8]; p.w_down = (const uint16_t*)d_in[9]; p.w_up = (const uint16_t*)d_in[10];
    p.out = (uint2*)d_out;
    p.E = in_sizes[3]; p.T = in_sizes[1];
    p.zero = 0;
    p.pairs = p.T / (2 * STEP); p.units = p.pairs + (NR / 2 + 1) * N1;
    bool fast = nsm >= NCTA && p.E <= E_CAP && p.E >= 8 && p.E % 2 == 0 && p.pairs >= 2 * N1 && p.units < 0xff00;
    static cudaTextureObject_t tex[3];
    static const void* tex_ptr[3];
    static int tex_n[3];
    for (int k = 0; k < 3 && fast; k++) {
        void* ptr = d_in[k == 2 ? 4 : 1 + k];
        if (tex_ptr[k] == ptr && tex_n[k] == p.T) continue;
        cudaResourceDesc rd = {};
        rd.resType = cudaResourceTypeLinear;
        rd.res.linear.devPtr = ptr;
        rd.res.linear.desc = k == 2 ? cudaCreateChannelDesc<uint2>() : cudaCreateChannelDesc<uint4>();
        rd.res.linear.sizeInBytes = (size_t)(p.T / 4) * (k == 2 ? 8 : 16);
        cudaTextureDesc td = {};
        td.readMode = cudaReadModeElementType;
        if (cudaCreateTextureObject(&tex[k], &rd, &td, nullptr) == cudaSuccess) { tex_ptr[k] = ptr; tex_n[k] = p.T; }
        else { cudaGetLastError(); tex_ptr[k] = nullptr; fast = false; }
    }
    p.tin = tex[0]; p.tout = tex[1]; p.tang = tex[2];
    if (!fast) {
        cudaMemsetAsync(d_out, 0, (size_t)p.E * 8);
        generic_scatter<<<nsm * 8, 256>>>(p);
        generic_finish<<<(p.E + 255) / 256, 256>>>(p);
        return;
    }
    void* args[] = {&p};
    cudaLaunchCooperativeKernel((const void*)main_kernel, dim3(NCTA), dim3(1024), args, SMEM_BYTES, cudaStreamPerThread);
}
```

```cpp
#include <cuda_runtime.h>
#include <cuda_bf16.h>
#include <stdint.h>

typedef unsigned long long u64;
constexpr uint32_t magic_of(uint32_t d) { return (uint32_t)(((1ull << 32) + d - 1) / d); }
constexpr uint32_t slice_of(uint32_t total, uint32_t n) {
    uint32_t d = ((total + n - 1) / n + 1) & ~1u;
    while (!((uint64_t)(n * d - 1) * magic_of(d) < ((uint64_t)n << 32))) d += 2;
    return d;
}
constexpr int E_CAP = 800000;
constexpr int NI = 32, NO = 28, NG = 2, IG = NI / NG;
constexpr uint32_t SI = slice_of(E_CAP, NI), SO = slice_of(E_CAP, NO);
constexpr uint32_t MI = magic_of(SI), MO = magic_of(SO);
constexpr int NCTA = 132, N2 = NI, N3 = NO * NG, N1 = NCTA - N2 - N3;
constexpr int C = 16, GB = NO * IG;
constexpr int NP = 5;
constexpr int NW = 28, STEP = NW * 256;
constexpr int NR = 4, LOGCAP = 8192, NCH = N1 * NW * NR * 8, KMAX = 4000;
static_assert(NR % 2 == 0 && NR >= 2 && NR <= 4 && NO % 4 == 0 && IG == 16, "shape");

constexpr int DA = 3, DS = 2, DV = 2, KA = DA * N1, KV = DV * N1, NSL = KA + KV + 1;
constexpr int ASEG = NO * C * 4, XSEG = IG * C * 2, VSEG = IG * C * 8;
constexpr int AG = IG * ASEG, XG = NO * XSEG, XO = IG / 2 * 4096, AXG = XO + XG + GB;
constexpr int PA = (AXG + 4095) / 4096, PV = NO * VSEG / 4096;
static_assert(2 * ASEG <= 4096 && AG == 2 * XG && (XO + XG) / 4096 == (AXG - 1) / 4096 && PA <= 15 && PV <= 14, "layout");
static_assert(DS >= DA - DV && DS <= DA && KA <= 256 && KV <= 128 && NSL <= 2 * NCTA && N1 <= 64, "ring");

constexpr uint32_t SB = 1024;
constexpr int SM_CNT = 0, SM_CB = NG * GB * 4, SM_LC = SM_CB + 2 * GB, SM_X = SM_LC + 256, SM_A = SM_X + NP * XG,
              SM_S1_END = SM_A + NP * AG;
constexpr int SM_AUX = SO * 8 + 512, QN = 256;
constexpr int AUX_Q = 0, AUX_PROG = QN * 8, AUX_CLS = AUX_PROG + 128, AUX_MISC = AUX_CLS + 576, AUX_DUMMY = AUX_MISC + 32,
              AUX_W = AUX_DUMMY + 256, AUX_END = AUX_W + 208;
constexpr int SMEM_BYTES = SM_AUX + AUX_END;
static_assert(SM_S1_END + 256 + NW * 256 <= SM_AUX && SMEM_BYTES <= 232448 && SM_X % 128 == 0 && AUX_W % 16 == 0, "smem");

__device__ __align__(8192) unsigned char g_ring[(size_t)(KA * PA + KV * PV + 1) * 8192];
__device__ __align__(8192) unsigned char g_probe[8192];
__device__ __align__(256) uint2 g_log[N1 * NW * LOGCAP];
__device__ uint32_t g_chunks[NCH];
__device__ __align__(128) uint2 g_agg[NO * SO];
__device__ uint2 g_info[NCTA];
__device__ __align__(128) uint32_t g_sync[160];
constexpr int SY_ZERO = 0, SY_END = 32, SY_EXIT = 64, SY_WORK = 96, SY_LOG = 128;
constexpr int FL_GO2 = 0, FL_GO3 = 1;
constexpr uint32_t FL_DATA = 0x10000;

__device__ __forceinline__ int lane_id() { int v; asm volatile("mov.u32 %0,%%laneid;" : "=r"(v)); return v; }
__device__ __forceinline__ int warp_id() { int v; asm volatile("mov.u32 %0,%%tid.x;" : "=r"(v)); return __shfl_sync(0xffffffffu, v >> 5, 0); }
__device__ __forceinline__ float bf_lo(uint32_t v) { return __uint_as_float(v << 16); }
__device__ __forceinline__ float bf_hi(uint32_t v) { return __uint_as_float(v & 0xffff0000u); }
__device__ __forceinline__ float rbf16(float x) { return __bfloat162float(__float2bfloat16_rn(x)); }
__device__ __forceinline__ uint32_t hmul2(uint32_t a, uint32_t b) {
    uint32_t d; asm("mul.rn.bf16x2 %0,%1,%2;" : "=r"(d) : "r"(a), "r"(b)); return d;
}
__device__ __forceinline__ uint32_t hadd2(uint32_t a, uint32_t b) {
    uint32_t d; asm("add.rn.bf16x2 %0,%1,%2;" : "=r"(d) : "r"(a), "r"(b)); return d;
}
__device__ __forceinline__ uint32_t dup_bf16(float x) {
    uint32_t d; asm("cvt.rn.bf16x2.f32 %0,%1,%1;" : "=r"(d) : "f"(x)); return d;
}
__device__ __forceinline__ uint32_t pack2(float lo, float hi) {
    uint32_t d; asm("cvt.rn.bf16x2.f32 %0,%2,%1;" : "=r"(d) : "f"(lo), "f"(hi)); return d;
}
__device__ __noinline__ float cos_slow(float x) { return cosf(x); }
__device__ __forceinline__ float cos_any(float x) { return fabsf(x) < 32.f ? __cosf(x) : cos_slow(x); }
__device__ __forceinline__ void bar_sync(int id, int n) { asm volatile("barrier.sync.aligned %0,%1;" ::"r"(id), "r"(n) : "memory"); }
__device__ __forceinline__ void bar_arrive(int id, int n) { asm volatile("barrier.arrive.aligned %0,%1;" ::"r"(id), "r"(n) : "memory"); }
__device__ __forceinline__ uint32_t ld_relaxed(const uint32_t* p) {
    uint32_t v; asm volatile("ld.relaxed.gpu.global.u32 %0,[%1];" : "=r"(v) : "l"(p) : "memory"); return v;
}
__device__ __forceinline__ void st128(void* p, uint4 v) {
    asm volatile("{.reg .b64 a,b; .reg .b128 q; mov.b64 a,{%1,%2}; mov.b64 b,{%3,%4}; mov.b128 q,{a,b}; st.relaxed.gpu.global.b128 [%0],q;}" ::"l"(p), "r"(v.x), "r"(v.y), "r"(v.z), "r"(v.w) : "memory");
}
__device__ __forceinline__ uint4 ld128(const void* p) {
    uint4 v;
    asm volatile("{.reg .b64 a,b; .reg .b128 q; ld.relaxed.gpu.global.b128 q,[%4]; mov.b128 {a,b},q; mov.b64 {%0,%1},a; mov.b64 {%2,%3},b;}" : "=r"(v.x), "=r"(v.y), "=r"(v.z), "=r"(v.w) : "l"(p) : "memory");
    return v;
}
__device__ __forceinline__ void wait_flag(const uint32_t* p, uint32_t want) {
    int spins = 0;
    while ((ld_relaxed(p) & 0xffff) < want) {
        __nanosleep(100);
        if (++spins > (1 << 22)) __trap();
    }
}
__device__ __forceinline__ uint32_t slot_a(int s) { return s * (PA * 8192); }
__device__ __forceinline__ uint32_t slot_v(int s) { return KA * PA * 8192 + s * (PV * 8192); }
__device__ __forceinline__ uint32_t ring_off(uint32_t clsg, uint32_t off) {
    return ((off >> 12) << 13) + (((clsg >> (off >> 12)) & 1) << 12) + (off & 4095);
}
__device__ __forceinline__ uint32_t cls_of(const unsigned char* sm, int s, int g) {
    return ((const uint16_t*)(sm + SM_AUX + AUX_CLS))[s] ^ (g ? ~0u : 0u);
}
__device__ __forceinline__ uint32_t flag_idx(const unsigned char* sm, int g, int type, int q) {
    return ring_off(cls_of(sm, NSL - 1, g), type * 1024 + q * 8) / 4;
}
__device__ __forceinline__ uint32_t* flags() { return (uint32_t*)(g_ring + slot_v(KV)); }
__device__ __forceinline__ uint32_t arrivals(int type, uint32_t k) {
    static_assert(DV == 2, "flag ring");
    return type == FL_GO3 ? IG * ((k >> 1) + 1) : NO * (k >> 1);
}
__device__ __forceinline__ bool elect_one() {
    uint32_t r; asm volatile("{.reg .pred p; elect.sync _|p,0xffffffff; selp.u32 %0,1,0,p;}" : "=r"(r)); return r;
}
template <int NCW, int TYPE, class F>
__device__ __forceinline__ void poller(const unsigned char* sm, int g, int blk0, int blk1, int units, int hook_at, F hook) {
    const int lane = lane_id();
    constexpr uint32_t aux = SB + SM_AUX;
    constexpr int DR = TYPE == FL_GO2 ? DS : DA;
    const uint32_t lt = (1u << lane) - 1;
    uint32_t ea[2][DR], ev[2][DV], k[2] = {0, 0}, want[2], v[2], fin[2], fout[2];
#pragma unroll
    for (int j = 0; j < 2; j++) {
        const int q = min(lane + j * 32, N1 - 1);
#pragma unroll
        for (int d = 0; d < DR; d++) {
            const uint32_t sa = q + d * N1, ca = cls_of(sm, sa, g);
            ea[j][d] = (((ca >> blk0) & 1) << 14) | (((ca >> blk1) & 1) << 15) | (sa << 16);
        }
#pragma unroll
        for (int d = 0; d < DV; d++) ev[j][d] = (cls_of(sm, KA + q + d * N1, g) & 0x3fff) | ((q + d * N1) << 24);
        want[j] = lane + j * 32 < N1 ? FL_DATA + arrivals(TYPE, 0) : ~0u;
        v[j] = 0;
        fin[j] = flag_idx(sm, g, TYPE, q); fout[j] = flag_idx(sm, g, TYPE ^ 1, q);
    }
    int tail = 0, check = min(min(QN - N1, hook_at), units), spins = 0;
    while (true) {
        bool hit[2]; uint32_t bal[2];
#pragma unroll
        for (int j = 0; j < 2; j++) {
            hit[j] = v[j] >= want[j] && (uint16_t)v[j] >= (uint16_t)want[j];
            bal[j] = __ballot_sync(0xffffffffu, hit[j]);
        }
        if (bal[0] | bal[1]) {
            asm volatile("fence.acquire.gpu;" ::: "memory");
            if (TYPE == FL_GO2) asm volatile("fence.proxy.async.global;" ::: "memory");
            asm volatile("fence.acq_rel.cta;" ::: "memory");
            spins = 0;
        } else if (++spins > (1 << 22)) __trap();
#pragma unroll
        for (int j = 0; j < 2; j++) {
            const uint32_t pos = tail + __popc(bal[j] & lt);
            const uint32_t hi = fout[j] | (k[j] & 1) | (k[j] < DV ? 0x8000 : 0) | ((pos + 1) << 16);
            asm volatile("{.reg .pred p; .reg .b64 q; setp.ne.u32 p,%3,0; mov.b64 q,{%1,%2}; @p st.relaxed.cta.shared.u64 [%0],q;}"
                         ::"r"(aux + AUX_Q + (pos % QN) * 8), "r"(ea[j][0] | ev[j][0]), "r"(hi), "r"((uint32_t)hit[j]) : "memory");
            tail += __popc(bal[j]);
            k[j] += hit[j];
        }
#pragma unroll
        for (int j = 0; j < 2; j++) v[j] = ld_relaxed(flags() + (fin[j] | (k[j] & 1)));
#pragma unroll
        for (int j = 0; j < 2; j++) {
            const uint32_t a0 = ea[j][0], v0 = ev[j][0] ^ 0x80000000u;
#pragma unroll
            for (int d = 0; d < DR; d++) ea[j][d] = hit[j] ? (d + 1 < DR ? ea[j][(d + 1) % DR] : a0) : ea[j][d];
#pragma unroll
            for (int d = 0; d < DV; d++) ev[j][d] = hit[j] ? (d + 1 < DV ? ev[j][(d + 1) % DV] : v0) : ev[j][d];
            want[j] = hit[j] ? ((k[j] >> 1) + 1) * FL_DATA + arrivals(TYPE, k[j]) : want[j];
        }
        if (tail >= check) {
            if (tail >= units) break;
            if (tail >= hook_at) { hook(); hook_at = 0x7fffffff; }
            int limit;
            do {
                int prog; asm volatile("ld.volatile.shared.u32 %0,[%1];" : "=r"(prog) : "r"(aux + AUX_PROG + min(lane, NCW - 1) * 4) : "memory");
                limit = __reduce_min_sync(0xffffffffu, prog) + QN - N1;
            } while (tail > limit);
            check = min(min(limit, hook_at), units);
        }
    }
}
template <bool BLOCK>
__device__ __forceinline__ bool next_unit(uint32_t aux, int warp, int t, int step, uint2& e) {
    u64 v;
    while (true) {
        asm volatile("ld.acquire.cta.shared.u64 %0,[%1];" : "=l"(v) : "r"(aux + AUX_Q + (t % QN) * 8) : "memory");
        if (__all_sync(0xffffffffu, (int)(v >> 48) == t + 1)) break;
        if (!BLOCK) return false;
        __nanosleep(40);
    }
    if (((t + step) ^ t) & 64) asm volatile("st.volatile.shared.u32 [%0],%1;" ::"r"(aux + AUX_PROG + warp * 4), "r"(t + step) : "memory");
    e = make_uint2((uint32_t)v, (uint32_t)(v >> 32) & 0xffff);
    return true;
}
__device__ __forceinline__ int upper_is_near(unsigned char* q) {
    ((uint4*)q)[0] = ((uint4*)q)[1] = ((uint4*)(q + 4096))[0] = ((uint4*)(q + 4096))[1] = make_uint4(0, 0, 0, 0);
    uint32_t best[2] = {~0u, ~0u};
#pragma unroll
    for (int r = 0; r < 4; r++) {
        uint32_t t0, t1, v;
        asm volatile("mov.u32 %0,%%clock;" : "=r"(t0)::"memory");
        asm volatile("atom.global.exch.b32 %0,[%1],0;" : "=r"(v) : "l"(q + (r & 1) * 4096) : "memory");
        asm volatile("{.reg .pred p; setp.eq.u32 p,%1,0xffffffff; @p trap; mov.u32 %0,%%clock;}" : "=r"(t1) : "r"(v) : "memory");
        best[r & 1] = min(best[r & 1], t1 - t0);
    }
    return best[1] < best[0];
}

struct Params {
    const uint2* m; const int* idx_in; const int* idx_out; const uint16_t* angle; const uint16_t* freq;
    const uint16_t *dist, *centers, *w_rbf, *w_sbf, *w_down, *w_up; uint2* out;
    int E, T, pairs, units;
    uint32_t zero;
    cudaTextureObject_t tin, tout, tang;
};

__device__ __forceinline__ void red_agg(uint32_t out, uint2 v, uint32_t c2) {
    asm volatile("red.global.add.noftz.v2.bf16x2 [%0],{%1,%2};" ::"l"(g_agg + out), "r"(hmul2(v.x, c2)), "r"(hmul2(v.y, c2)) : "memory");
}
__device__ __forceinline__ void decode_entry(uint32_t e0, uint32_t e1, uint32_t& in, uint32_t& out) {
    const uint32_t bx = e1 >> 21, g = bx >= GB, rem = bx - g * GB;
    in = (g * IG + rem % IG) * SI + (e0 & 0xffff);
    out = rem / IG * SO + (e1 & 0xffff);
}
__device__ __forceinline__ void wait_zeroed() {
    wait_flag(&g_sync[SY_ZERO], N3);
    asm volatile("fence.acquire.gpu;" ::: "memory");
}
constexpr int BAR_ATOMS = 1, BAR_STS = 2, BAR_PUB = 4, BAR_PUBFREE = 6, BAR_W = 8, BAR_LOG = 9;
constexpr int NT_STS = (NW + 2) * 32, NT_ATOMS = (NW + 1) * 32;
__device__ __forceinline__ void mbar_arrive(uint32_t bar) {
    __syncwarp();
    if (elect_one()) asm volatile("mbarrier.arrive.shared::cta.b64 _,[%0];" ::"r"(bar) : "memory");
}
__device__ __forceinline__ void mbar_wait(uint32_t bar, uint32_t parity) {
    asm volatile("{.reg .pred p; .reg .u32 n; mbarrier.try_wait.parity.shared::cta.b64 p,[%0],%1; @p bra D; mov.u32 n,0;\n"
                 "W: mbarrier.try_wait.parity.shared::cta.b64 p,[%0],%1,2000; @p bra D;\n"
                 "add.u32 n,n,1; setp.lt.u32 p,n,0x4000000; @p bra W; trap;\nD:}" ::"r"(bar), "r"(parity) : "memory");
}
__device__ __forceinline__ uint32_t mad(uint32_t a, uint32_t b, uint32_t c) {
    uint32_t d; asm("mad.lo.u32 %0,%1,%2,%3;" : "=r"(d) : "r"(a), "r"(b), "r"(c)); return d;
}
template <bool R, int G> struct Kind { static constexpr bool replay = R; static constexpr int group = G; };

__device__ __forceinline__ void stage1(const Params& p, unsigned char* sm, int pid) {
    const int warp = warp_id(), lane = lane_id();
    constexpr uint32_t sb = SB;
    uint4 ra[2], rb[2]; uint2 rc[2];
    volatile int* const s_next = (volatile int*)(sm + SM_LC + 64);
    const int total = p.pairs * 2, snap = total - 2 * 2 * N1, sw = pid & 1;
    u64* const logsync = (u64*)&g_sync[SY_LOG];
    constexpr uint32_t mb = sb + SM_LC;
    if (threadIdx.x < 4) asm volatile("mbarrier.init.shared::cta.b64 [%0],1;" ::"r"(mb + threadIdx.x * 8) : "memory");
    if (threadIdx.x == 0) s_next[2] = s_next[3] = 0x7ffffff0;
    if (threadIdx.x < 32) s_next[16 + threadIdx.x] = 2 * C;
    __syncthreads();
    if (warp < NW) {
        constexpr uint32_t cb = sb + SM_CNT, xdum = (uint32_t)(SM_LC + 128 - SM_CNT) << 19;
        constexpr uint32_t xk = sb + SM_X, ak = sb + SM_A - 2 * xk;
        uint32_t cur0 = xk + sw * XG + (lane & p.zero), nxt0 = cur0 + 2 * XG - C * 2, cur1 = cur0 - sw * 2 * XG, nxt1 = cur1 + 2 * XG - C * 2;
        uint32_t fresh = xk + 4 * XG - C * 2 + (lane & p.zero), n0 = 0, wpos = 0, chunk = 0;
        int h_in = pid * 2, np = 0;
        uint2* const log = g_log + (pid * NW + warp) * LOGCAP;
        const uint32_t ltmask = ((1u << lane) - 1) | p.zero, tq = (warp * 64 + lane) | p.zero;
        auto load_in = [&](int h) {
            const int q = h_in * (STEP / 4) + tq + h * 32;
            asm volatile("tex.1d.v4.u32.s32 {%0,%1,%2,%3},[%4,{%5}];" : "=r"(ra[h].x), "=r"(ra[h].y), "=r"(ra[h].z), "=r"(ra[h].w) : "l"(p.tin), "r"(q));
            asm volatile("tex.1d.v4.u32.s32 {%0,%1,%2,%3},[%4,{%5}];" : "=r"(rb[h].x), "=r"(rb[h].y), "=r"(rb[h].z), "=r"(rb[h].w) : "l"(p.tout), "r"(q));
            asm volatile("{.reg .b32 z,w; tex.1d.v4.u32.s32 {%0,%1,z,w},[%2,{%3}];}" : "=r"(rc[h].x), "=r"(rc[h].y) : "l"(p.tang), "r"(q));
        };
        const uint32_t stage = sb + SM_S1_END + 256 + warp * 256;
        auto flush_stage = [&]() {
            uint2 e;
            __syncwarp();
            asm volatile("ld.shared.v2.u32 {%0,%1},[%2];" : "=r"(e.x), "=r"(e.y) : "r"(stage + lane * 8) : "memory");
            log[(wpos & ~31u) + lane] = e;
            __syncwarp();
        };
        auto direct = [&](uint32_t first, uint32_t stride, uint32_t count, auto range, auto gate) {
            const float f = bf_lo(p.freq[0]);
            for (uint32_t c0 = first;; c0 += stride * 4) {
                uint2 e[4], v[4]; uint32_t ok = 0, big = 0;
#pragma unroll
                for (int k = 0; k < 4; k++) {
                    uint32_t lo = 0, hi = 0;
                    if (c0 + k * stride < count) range(c0 + k * stride, lo, hi);
                    e[k] = make_uint2(0, 0);
                    if (lo + lane < hi) { e[k] = __ldcg(g_log + lo + lane); ok |= 1u << k; }
                }
                __syncwarp();
                if (c0 == first) gate();
#pragma unroll
                for (int k = 0; k < 4; k++) {
                    uint32_t in;
                    decode_entry(e[k].x, e[k].y, in, e[k].y);
                    v[k] = __ldcg(p.m + in);
                    e[k].x = __float_as_uint(rbf16(f * bf_hi(e[k].x)));
                    big = max(big, e[k].x & 0x7fffffffu);
                }
                const bool slow = __any_sync(0xffffffffu, big >= 0x42000000u);
#pragma unroll
                for (int k = 0; k < 4; k++) {
                    float c = __cosf(__uint_as_float(e[k].x));
                    if (slow) c = cos_slow(__uint_as_float(e[k].x));
                    if ((ok >> k) & 1) red_agg(e[k].y, v[k], dup_bf16(c));
                }
                __syncwarp();
                if (c0 + stride * 4 >= count) break;
            }
        };
        auto drain = [&]() {
            const uint32_t lb = (pid * NW + warp) * LOGCAP;
            if (wpos & 31) flush_stage();
            direct(0, 1, (wpos - n0 + 31) / 32, [&](uint32_t c, uint32_t& lo, uint32_t& hi) { lo = lb + n0 + c * 32; hi = lb + wpos; },
                   [&] { wait_zeroed(); __syncwarp(); });
            wpos = n0;
        };
        auto load_log = [&](int j) {
            uint2 e[8];
#pragma unroll
            for (int k = 0; k < 8; k++) {
                const uint32_t ch = __shfl_sync(0xffffffffu, chunk, k * NR + j);
                e[k] = make_uint2(0, xdum + (lane << 21));
                if (j < NR && ch) e[k] = __ldcg(g_log + (ch - 1) * 32 + lane);
            }
#pragma unroll
            for (int h = 0; h < 2; h++) {
                ra[h] = make_uint4(e[h * 4].x, e[h * 4].y, e[h * 4 + 1].x, e[h * 4 + 1].y);
                rb[h] = make_uint4(e[h * 4 + 2].x, e[h * 4 + 2].y, e[h * 4 + 3].x, e[h * 4 + 3].y);
            }
        };
        auto step = [&](const int k2, auto kind) {
            constexpr bool R = decltype(kind)::replay;
            constexpr int G = decltype(kind)::group;
            uint32_t pa[8], aw[8], xw[8], r[8];
#pragma unroll
            for (int h = 0; h < 2; h++) {
                if (!R) {
                    const uint32_t in[4] = {ra[h].x, ra[h].y, ra[h].z, ra[h].w}, out[4] = {rb[h].x, rb[h].y, rb[h].z, rb[h].w};
#pragma unroll
                    for (int k = 0; k < 4; k++) {
                        const uint32_t i = __umulhi(in[k], MI), o = __umulhi(out[k], MO);
                        aw[h * 4 + k] = __byte_perm(in[k] - i * SI, k < 2 ? rc[h].x : rc[h].y, (k & 1) ? 0x7610 : 0x5410);
                        pa[h * 4 + k] = mad(i, NO, o);
                        xw[h * 4 + k] = mad(i, 1u << 21, mad(o, (IG << 21) - SO, out[k]));
                        asm("{.reg .pred p; setp.ge.u32 p,%1,%2; @p add.u32 %0,%0,%3;}" : "+r"(xw[h * 4 + k]) : "r"(in[k]), "n"(IG * SI), "n"((GB - IG) << 21));
                    }
                } else {
#pragma unroll
                    for (int k = h * 4; k < h * 4 + 4; k++) {
                        const uint4 q4 = (k & 2) ? rb[h] : ra[h];
                        const uint2 e = (k & 1) ? make_uint2(q4.z, q4.w) : make_uint2(q4.x, q4.y);
                        aw[k] = e.x; xw[k] = e.y;
                        pa[k] = mad((e.y >> 21) % IG, NO, (e.y >> 25) + (e.y >= GB << 21 ? GB - NO : 0));
                    }
                }
                if (h == 0) {
                    mbar_wait(mb + G * 8, k2 & 1);
                    if (!R) {
                        if (G) asm volatile("ld.volatile.shared.u32 %0,[%1];" : "=r"(h_in) : "r"(mb + 64) : "memory");
                        else h_in++;
                    }
                }
#pragma unroll
                for (int k = h * 4; k < h * 4 + 4; k++)
                    asm volatile("atom.shared.add.u32 %0,[%1+%2],1;" : "=r"(r[k]) : "r"(xw[k] >> 19), "n"(cb) : "memory");
            }
            bar_arrive(BAR_ATOMS, NT_ATOMS);
            mbar_wait(mb + 16 + G * 8, k2 & 1);
            if (!R) {
                load_in(0);
                if (p.zero) __nanosleep(0);
            }
            uint32_t ovf = 0;
#pragma unroll
            for (int k = 0; k < 8; k++) {
                const bool lo = r[k] < C, hi = xw[k] >= GB << 21;
                const uint32_t s2 = r[k] * 2 + (hi ? (lo ? cur1 : nxt1) : (lo ? cur0 : nxt0));
                asm volatile("{.reg .pred p; .reg .b16 a,b; setp.lt.u32 p,%5,%6; mov.b32 {a,b},%4;"
                             " @p st.shared.u32 [%1+%8],%2; @p st.shared.u16 [%3],a; @!p or.b32 %0,%0,%7;}"
                             : "+r"(ovf) : "r"(mad(pa[k], C * 2, s2) * 2), "r"(aw[k]), "r"((xw[k] >> 16) + s2), "r"(xw[k]), "r"(r[k]),
                               "n"(2 * C), "r"(R && xw[k] >= xdum ? 0u : 1u << k), "n"(ak) : "memory");
            }
            bar_arrive(BAR_STS + G, NT_STS);
            if (!R) {
                if (p.zero) __nanosleep(0);
                load_in(1);
            }
            uint32_t bal = __ballot_sync(0xffffffffu, ovf != 0);
            while (bal) {
                uint32_t e0 = aw[7], e1 = xw[7];
#pragma unroll
                for (int k = 6; k >= 0; k--)
                    if (ovf & (1u << k)) { e0 = aw[k]; e1 = xw[k]; }
                const uint32_t pos = ovf ? (wpos & 31) + __popc(bal & ltmask) : 64, next = wpos + __popc(bal);
                asm volatile("{.reg .pred p; setp.lt.u32 p,%3,32; @p st.shared.v2.u32 [%0],{%1,%2};}" ::"r"(stage + pos * 8), "r"(e0), "r"(e1), "r"(pos) : "memory");
                if ((next ^ wpos) & 32) {
                    flush_stage();
                    asm volatile("{.reg .pred p; setp.lt.u32 p,%3,32; @p st.shared.v2.u32 [%0],{%1,%2};}" ::"r"(stage + (pos - 32) * 8), "r"(e0), "r"(e1), "r"(pos - 32) : "memory");
                }
                wpos = next;
                ovf &= ovf - 1;
                bal = __ballot_sync(0xffffffffu, ovf != 0);
            }
            if (R) load_log((k2 - np) * 2 + G + 1);
            if (G || !R || k2 != np + NR / 2 - 1) {
                if (G != sw) { cur1 = nxt1 + C * 2; nxt1 = fresh - XG; } else { cur0 = nxt0 + C * 2; nxt0 = fresh; }
            }
            fresh += fresh == xk + (NP - 1) * XG - C * 2 ? -(NP - 1) * XG : XG;
        };
        for (int stop = snap; h_in < total;) {
            load_in(0); load_in(1);
            while (true) {
                step(np, Kind<false, 0>());
                step(np, Kind<false, 1>());
                np++;
                if (h_in < stop && wpos <= LOGCAP - 512) continue;
                if (h_in >= stop && stop < total) {
                    const uint32_t nch = min(wpos / 32, (LOGCAP - 256 * NR) / 32);
                    uint32_t base = 0;
                    if (lane == 0) base = (uint32_t)atomicAdd(logsync, (u64)nch);
                    base = __shfl_sync(0xffffffffu, base, 0);
                    const uint32_t mine = min(nch, NCH - min(base, NCH));
                    for (uint32_t c = lane; c < mine; c += 32) g_chunks[base + c] = (pid * NW + warp) * (LOGCAP / 32) + c + 1;
                    n0 = mine * 32;
                    __syncwarp();
                    if (n0 && elect_one()) asm volatile("cp.async.bulk.prefetch.L2.global [%0],%1;" ::"l"(log), "r"(n0 * 8) : "memory");
                    __syncwarp();
                    bar_arrive(BAR_LOG, (NW + 1) * 32);
                    stop = total;
                }
                if (h_in >= total || wpos > LOGCAP - 512) break;
            }
            if (wpos > LOGCAP - 512) drain();
        }
        {
            u64 v; int spins = 0;
            do {
                asm volatile("ld.acquire.gpu.global.u64 %0,[%1];" : "=l"(v) : "l"(logsync) : "memory");
                if (++spins > (1 << 22)) __trap();
            } while ((v >> 32) < N1);
            const uint32_t idx = (((lane / NR) * NW + warp) * NR + lane % NR) * N1 + pid;
            if (lane < 8 * NR && idx < (uint32_t)v) chunk = __ldcg(g_chunks + idx);
            __syncwarp();
        }
        if (wpos > LOGCAP - 256 * NR) drain();
        load_log(0);
#pragma unroll 1
        for (int k2 = np; k2 < np + NR / 2; k2++) {
            step(k2, Kind<true, 0>());
            step(k2, Kind<true, 1>());
        }
        uint2* const rng = (uint2*)(sm + SM_S1_END);
        if (lane == 0) rng[warp] = make_uint2(n0, wpos);
        if (wpos & 31) flush_stage();
        __syncwarp();
        for (int g = 0; g < NG; g++) {
            mbar_wait(mb + g * 8, (np + NR / 2) & 1);
            mbar_wait(mb + 16 + g * 8, (np + NR / 2) & 1);
            bar_arrive(BAR_ATOMS, NT_ATOMS);
            bar_arrive(BAR_STS + g, NT_STS);
        }
        const uint2 mine = lane < NW ? rng[lane] : make_uint2(0, 0);
        const uint32_t nch = (mine.y - mine.x + 31) / 32;
        uint32_t end = nch;
#pragma unroll
        for (int d = 1; d < 32; d *= 2) {
            const uint32_t t = __shfl_up_sync(0xffffffffu, end, d);
            if (lane >= d) end += t;
        }
        direct(warp, NW, __shfl_sync(0xffffffffu, end, 31), [&](uint32_t c, uint32_t& lo, uint32_t& hi) {
            const int w = __popc(__ballot_sync(0xffffffffu, end <= c));
            const uint32_t lb = (pid * NW + w) * LOGCAP;
            lo = lb + __shfl_sync(0xffffffffu, mine.x + (c - (end - nch)) * 32, w);
            hi = lb + __shfl_sync(0xffffffffu, mine.y, w);
        }, [&] { bar_sync(BAR_W, (NW + 1) * 32); });
    } else if (warp == NW) {
        const int row = min(lane, NO - 1), swz = (row >> 1) & 3;
        mbar_arrive(mb);
        int pn = N1 + pid, pnn = 0, nc = 0x7ffffff0;
        for (int s = 0; s < nc; s++) {
            const int hn = min(pn * 2 + (s & 1), total);
            if (hn == total) nc = min(nc, s + 2 + NR + 2);
            const uint32_t sub = s == nc - 4 ? 0 : C, bias = s == nc - 2 ? C : 0;
            uint4* cp = (uint4*)(sm + SM_CNT + ((s ^ sw) & 1) * GB * 4) + row * 4;
            bar_sync(BAR_ATOMS, NT_ATOMS);
            uint4 c[4];
#pragma unroll
            for (int j = 0; j < 4; j++) c[j] = cp[j ^ swz];
            __syncwarp();
#pragma unroll
            for (int j = 0; j < 4; j++)
                cp[j ^ swz] = make_uint4(min(max(c[j].x, C), 2 * C) - sub, min(max(c[j].y, C), 2 * C) - sub,
                                         min(max(c[j].z, C), 2 * C) - sub, min(max(c[j].w, C), 2 * C) - sub);
            if (lane == 0 && !(s & 1)) {
                s_next[0] = hn; s_next[2] = nc;
                if (hn >= snap) s_next[3] = min(s_next[3], s + 1);
            }
            mbar_arrive(mb + ((s + 1) & 1) * 8);
            uint4 w = make_uint4(0, 0, 0, 0);
#pragma unroll
            for (int j = 0; j < 4; j++) {
                const int sh = (j ^ swz) * 8;
                w.x |= min(c[j].x - bias, C) << sh; w.y |= min(c[j].y - bias, C) << sh;
                w.z |= min(c[j].z - bias, C) << sh; w.w |= min(c[j].w - bias, C) << sh;
            }
            mbar_wait(mb + 16 + (s & 1) * 8, (s >> 1) & 1);
            ((uint4*)(sm + SM_CB + (s & 1) * GB))[row] = w;
            bar_arrive(BAR_STS + (s & 1), NT_STS);
            if (s & 1) pn = min(2 * N1 + __shfl_sync(0xffffffffu, pnn, 0), p.pairs);
            else if (hn < total && s / 2 + 2 < KMAX) {
                if (lane == 0) asm volatile("atom.relaxed.gpu.global.add.u32 %0,[%1],1;" : "=r"(pnn) : "l"(&g_sync[SY_WORK]) : "memory");
            } else pnn = p.pairs;
            const int hp = pn * 2 + ((s & 1) ^ 1);
            if (hp < total && elect_one())
                asm volatile("cp.async.bulk.prefetch.L2.global [%0],%1;" ::"l"(p.angle + hp * STEP), "r"(STEP * 2) : "memory");
            __syncwarp();
        }
    } else if (warp < NW + 3) {
        const int par = warp - NW - 1, g = par ^ sw;
        mbar_arrive(mb + 16 + par * 8);
        const uint32_t* const fb = flags() + flag_idx(sm, g, lane & 1, pid);
        for (int s = par; s < s_next[2]; s += 2) {
            const int k = s >> 1, slot = k % DA * N1 + pid, slots = k % DS * N1 + pid, pl = s % NP;
            const uint32_t cls = __shfl_sync(0xffffffffu, cls_of(sm, slot, g), 0), clss = __shfl_sync(0xffffffffu, cls_of(sm, slots, g), 0);
            if (k >= DS) {
                const uint32_t kw = k - ((lane & 1) ? DS : DA - DV);
                wait_flag(fb + (kw & 1), arrivals(lane & 1, kw));
                __syncwarp();
                asm volatile("fence.proxy.async.global;" ::: "memory");
            }
            bar_sync(BAR_STS + par, NT_STS);
            asm volatile("fence.proxy.async.shared::cta;" ::: "memory");
            if (elect_one()) {
                unsigned char* dst = g_ring + slot_a(slot);
#pragma unroll
                for (int j = 0; j < IG / 2; j++)
                    asm volatile("cp.async.bulk.global.shared::cta.bulk_group [%0],[%1],%2;" ::"l"(g_ring + slot_a(slots) + ring_off(clss, j * 4096)),
                                 "r"(sb + SM_A + pl * AG + j * 2 * ASEG), "n"(2 * ASEG) : "memory");
#pragma unroll
                for (int j = 0; j * 4096 < XG; j++)
                    asm volatile("cp.async.bulk.global.shared::cta.bulk_group [%0],[%1],%2;" ::"l"(dst + ring_off(cls, XO + j * 4096)),
                                 "r"(sb + SM_X + pl * XG + j * 4096), "r"(min(4096, XG - j * 4096)) : "memory");
                asm volatile("cp.async.bulk.global.shared::cta.bulk_group [%0],[%1],%2;" ::"l"(dst + ring_off(cls, XO + XG)),
                             "r"(sb + SM_CB + par * GB), "r"(GB) : "memory");
                asm volatile("cp.async.bulk.commit_group;" ::: "memory");
                asm volatile("cp.async.bulk.wait_group 0;" ::: "memory");
            }
            __syncwarp();
            mbar_arrive(mb + 16 + par * 8);
            bar_sync(BAR_PUBFREE + par, 64);
            bar_arrive(BAR_PUB + par, 64);
        }
    } else if (warp == NW + 3) {
        uint32_t* const fb = flags() + flag_idx(sm, (lane >> 1) & 1, lane & 1, pid);
        bar_arrive(BAR_PUBFREE, 64);
        bar_arrive(BAR_PUBFREE + 1, 64);
        for (int s = 0; s < s_next[2]; s++) {
            if (s == 4) { wait_zeroed(); __syncwarp(); }
            const int g = (s ^ sw) & 1;
            bar_sync(BAR_PUB + (s & 1), 64);
            if (s + 2 < s_next[2]) bar_arrive(BAR_PUBFREE + (s & 1), 64);
            const bool pooled = s == s_next[3];
            if (pooled) bar_sync(BAR_LOG, (NW + 1) * 32);
            asm volatile("fence.release.gpu;" ::: "memory");
            if ((lane >> 1) == g) asm volatile("red.relaxed.gpu.global.add.u32 [%0],%1;" ::"l"(fb + ((s >> 1) & 1)), "r"(FL_DATA) : "memory");
            if (pooled && lane == 0) asm volatile("red.relaxed.gpu.global.add.u64 [%0],%1;" ::"l"(logsync), "l"(1ull << 32) : "memory");
            __syncwarp();
        }
        bar_arrive(BAR_W, (NW + 1) * 32);
    }
}

__device__ __forceinline__ void stage2(const Params& p, unsigned char* sm, int g, int ig) {
    const int warp = warp_id(), lane = lane_id();
    constexpr uint32_t sb = SB;
    constexpr int NCW = 16, STEPS = NO / 4, TAB = NCW * ASEG, MB = TAB + SI * 8;
    static_assert(MB + 8 * NCW + 8 <= SM_AUX && MB % 8 == 0, "stage2 smem");
    if (threadIdx.x <= NCW) asm volatile("mbarrier.init.shared::cta.b64 [%0],1;" ::"r"(sb + MB + threadIdx.x * 8) : "memory");
    asm volatile("fence.proxy.async.shared::cta;" ::: "memory");
    __syncthreads();
    if (warp == 30) {
        const int e0 = (g * IG + ig) * SI, bytes = max(0, min((int)SI, p.E - e0)) * 8;
        if (elect_one()) {
            asm volatile("mbarrier.arrive.expect_tx.shared::cta.b64 _,[%0],%1;" ::"r"(sb + MB + NCW * 8), "r"(bytes) : "memory");
            for (int o = 0; o < bytes; o += 16384)
                asm volatile("cp.async.bulk.shared::cluster.global.mbarrier::complete_tx::bytes [%0],[%1],%2,[%3];" ::"r"(sb + TAB + o), "l"((const char*)(p.m + e0) + o), "r"(min(16384, bytes - o)), "r"(sb + MB + NCW * 8) : "memory");
        }
        __syncwarp();
    }
    if (warp == 31) poller<NCW, FL_GO2>(sm, g, ig >> 1, 0, p.units, p.units - 3 * N1, [&] {
            const int e0 = (g * IG + ig) * SI, n = min((int)SI, p.E - e0);
            if (n > 0 && elect_one()) asm volatile("cp.async.bulk.prefetch.L2.global [%0],%1;" ::"l"(p.m + e0), "r"(n * 8) : "memory");
            __syncwarp();
        });
    if (warp >= NCW) return;
    const uint32_t f2 = (uint32_t)p.freq[0] * 0x10001u;
    const uint32_t vlane = slot_v(0) + (lane >> 4) * 8192 + ((lane >> 3) & 1) * VSEG + ig * 128 + (lane & 7) * 16;
    const uint32_t aoff = (ig >> 1) * 8192 + (ig & 1) * ASEG, buf = sb + warp * ASEG, mb = sb + MB + warp * 8;
    auto fetch = [&](uint32_t e) {
        if (elect_one()) {
            asm volatile("mbarrier.arrive.expect_tx.shared::cta.b64 _,[%0],%1;" ::"r"(mb), "n"(ASEG) : "memory");
            asm volatile("cp.async.bulk.shared::cluster.global.mbarrier::complete_tx::bytes [%0],[%1],%2,[%3];" ::"r"(buf),
                         "l"(g_ring + (slot_a((e >> 16) & 0xff) + aoff + ((e >> 2) & 0x1000))), "n"(ASEG), "r"(mb) : "memory");
        }
        __syncwarp();
    };
    mbar_wait(sb + MB + NCW * 8, 0);
    uint2 qn = make_uint2(0, 0);
    bool have = false;
    uint32_t ph = 0;
    for (int t = warp; t < p.units; t += NCW) {
        if (!have) { next_unit<true>(sb + SM_AUX, warp, t, NCW, qn); fetch(qn.x); }
        const uint2 qe = qn;
        mbar_wait(mb, ph); ph ^= 1;
        uint2 a[STEPS];
#pragma unroll
        for (int j = 0; j < STEPS; j++) asm volatile("ld.shared.v2.u32 {%0,%1},[%2];" : "=r"(a[j].x), "=r"(a[j].y) : "r"(buf + j * 256 + lane * 8) : "memory");
        have = next_unit<false>(sb + SM_AUX, warp, t + NCW, NCW, qn);
        uint32_t big = 0, x2[STEPS];
#pragma unroll
        for (int j = 0; j < STEPS; j++) {
            x2[j] = hmul2(__byte_perm(a[j].x, a[j].y, 0x7632), f2);
            a[j].x = __byte_perm(a[j].x, a[j].y, 0x5410);
            big |= (x2[j] & 0x7fff7fffu) + 0x3e003e00u;
        }
        const bool slow = __any_sync(0xffffffffu, big & 0x80008000u);
        if (have) fetch(qn.x + ((uint32_t)slow & p.zero));
        if (slow) {
#pragma unroll
            for (int j = 0; j < STEPS; j++) x2[j] = pack2(cos_slow(bf_lo(x2[j])), cos_slow(bf_hi(x2[j])));
        }
        const uint32_t tag = qe.x >> 31, cq = (qe.x >> (lane >> 4)) << 12;
        const uint32_t vo = ((qe.x >> 24) & 0x7f) * (PV * 8192) + vlane;
        uint2 m0[STEPS], m1[STEPS];
#pragma unroll
        for (int jj = 0; jj < STEPS + 1; jj++) {
            if (jj < STEPS) {
                asm volatile("ld.shared.v2.u32 {%0,%1},[%2];" : "=r"(m0[jj].x), "=r"(m0[jj].y) : "r"(sb + TAB + (a[jj].x & 0xffff) * 8) : "memory");
                asm volatile("ld.shared.v2.u32 {%0,%1},[%2];" : "=r"(m1[jj].x), "=r"(m1[jj].y) : "r"(sb + TAB + (a[jj].x >> 16) * 8) : "memory");
            }
            if (jj >= 1) {
                const int j = jj - 1;
                const uint32_t cf = pack2(__cosf(bf_lo(x2[j])), __cosf(bf_hi(x2[j]))), c2 = slow ? x2[j] : cf;
                const uint32_t d0 = __byte_perm(c2, 0, 0x1010), d1 = __byte_perm(c2, 0, 0x3232);
                st128(g_ring + (vo | ((cq >> (2 * j)) & 0x1000)) + j * 16384,
                      make_uint4((hmul2(m0[j].x, d0) & ~1u) | tag, hmul2(m0[j].y, d0), hmul2(m1[j].x, d1), hmul2(m1[j].y, d1)));
                if (p.zero) __nanosleep(0);
            }
        }
        __syncwarp();
        if (qe.y & 0x8000) asm volatile("fence.acq_rel.gpu;" ::: "memory");
        if (lane == 0) asm volatile("red.relaxed.gpu.global.add.u32 [%0],1;" ::"l"(flags() + (qe.y & 0x7fff)) : "memory");
    }
}

constexpr int EXPORT_LO = 20, EXPORT_N = 31 - EXPORT_LO;
__device__ __forceinline__ uint2 lock64(uint32_t a) {
    uint2 r;
    asm volatile("{.reg .b64 y; atom.shared.exch.b64 y,[%2],0xffffffffffffffff; mov.b64 {%0,%1},y;}" : "=r"(r.x), "=r"(r.y) : "r"(a) : "memory");
    return r;
}

__device__ __forceinline__ void stage3(const Params& p, unsigned char* sm, int g, int o) {
    const int warp = warp_id(), lane = lane_id();
    constexpr uint32_t sb = SB;
    if (threadIdx.x < 64) ((uint32_t*)(sm + SM_AUX + AUX_DUMMY))[threadIdx.x] = ~0u;
    for (int i = (g * NO + o) * 1024 + threadIdx.x; i < NO * (int)SO / 2; i += N3 * 1024) ((uint4*)g_agg)[i] = make_uint4(0, 0, 0, 0);
    __syncthreads();
    if (threadIdx.x == 0) asm volatile("red.release.gpu.global.add.u32 [%0],1;" ::"l"(&g_sync[SY_ZERO]) : "memory");
    const int t0 = p.pairs * 2 * STEP + (g * NO + o) * 1024 + threadIdx.x;
    static_assert(2 * STEP <= N3 * 1024, "remainder");
    if (t0 - lane < p.T) {
        const int t = min(t0, p.T - 1);
        const uint2 v = __ldg(p.m + p.idx_in[t]);
        wait_zeroed();
        if (t0 < p.T) red_agg(p.idx_out[t], v, dup_bf16(cos_any(rbf16(bf_lo(p.freq[0]) * bf_lo(p.angle[t])))));
        __syncwarp();
    }
    constexpr int NCW = EXPORT_LO, STEPS = IG / 4;
    if (warp == 31) {
        poller<NCW, FL_GO3>(sm, g, (XO + o * XSEG) >> 12, (XO + XG) >> 12, p.units, p.units - 2 * N1, [&] {
            constexpr int H = (SO / 2 + 7) & ~7;
            const int e0 = (o * SO + g * H) & ~7, n = min(H + 8, p.E - e0) & ~7;
            if (n > 0 && elect_one()) {
                asm volatile("cp.async.bulk.prefetch.L2.global [%0],%1;" ::"l"(g_agg + e0), "r"(n * 8) : "memory");
                asm volatile("cp.async.bulk.prefetch.L2.global [%0],%1;" ::"l"(p.dist + e0), "r"(n * 2) : "memory");
            }
            __syncwarp();
        });
    } else if (warp < NCW) {
        const uint32_t dummy = sb + SM_AUX + AUX_DUMMY + lane * 8, r0 = (lane & 7) * 2;
        const uint32_t vlane = slot_v(0) + ring_off(0, o * VSEG) + lane * 16, xlane = ring_off(0, XO + o * XSEG) + lane * 4;
        const uint32_t clane = ring_off(0, XO + XG + o * IG) + (lane >> 3) * 4;
        for (int t = warp; t < p.units; t += NCW) {
            uint2 qe;
            next_unit<true>(sb + SM_AUX, warp, t, NCW, qe);
            const uint32_t tag = qe.x >> 31, ab = slot_a((qe.x >> 16) & 0xff);
            const uint4* vp = (const uint4*)(g_ring + (((qe.x >> 24) & 0x7f) * (PV * 8192) + vlane + (((qe.x >> (o >> 1)) & 1) << 12)));
            const uint32_t* xp = (const uint32_t*)(g_ring + (ab + xlane + ((qe.x >> 2) & 0x1000)));
            const uint32_t* cp = (const uint32_t*)(g_ring + (ab + clane + ((qe.x >> 3) & 0x1000)));
            uint4 v[STEPS]; uint32_t x[STEPS];
            const uint32_t cn = __ldcg(cp);
#pragma unroll
            for (int j = 0; j < STEPS; j++) x[j] = __ldcg(xp + j * 32);
#pragma unroll
            for (int j = 0; j < STEPS; j++) v[j] = ld128(vp + j * 32);
            for (int spins = 0;; spins++) {
                uint32_t bad = 0;
#pragma unroll
                for (int j = 0; j < STEPS; j++) bad |= v[j].x ^ tag;
                if (!__any_sync(0xffffffffu, bad & 1)) break;
                if (spins > (1 << 22)) __trap();
#pragma unroll
                for (int j = 0; j < STEPS; j++) v[j] = ld128(vp + j * 32);
            }
            uint32_t ad[2 * STEPS], dep = cn;
#pragma unroll
            for (int j = 0; j < STEPS; j++) {
                const uint32_t c = (cn >> (8 * j)) & 0xff;
                ad[2 * j] = r0 < c ? sb + (x[j] & 0xffff) * 8 : dummy;
                ad[2 * j + 1] = r0 + 1 < c ? sb + (x[j] >> 16) * 8 : dummy;
                dep ^= x[j];
            }
            if (lane == 0) asm volatile("red.relaxed.gpu.global.add.u32 [%0],%1;" ::"l"(flags() + (qe.y & 0x7fff)), "r"(1 + (dep & p.zero)) : "memory");
            uint32_t pend = 0;
#pragma unroll
            for (int j0 = 0; j0 < 2 * STEPS; j0 += 4) {
                uint2 t[4];
#pragma unroll
                for (int j = 0; j < 4; j++) t[j] = lock64(ad[j0 + j]);
#pragma unroll
                for (int j = 0; j < 4; j++) {
                    const int jj = j0 + j;
                    const uint32_t vx = (jj & 1) ? v[jj / 2].z : v[jj / 2].x, vy = (jj & 1) ? v[jj / 2].w : v[jj / 2].y;
                    asm volatile("{.reg .pred p,q; setp.ne.u32 p,%4,0xffffffff; @p st.shared.v2.u32 [%1],{%2,%3}; setp.ne.and.u32 q,%1,%5,!p; @q or.b32 %0,%0,%6;}"
                                 : "+r"(pend) : "r"(ad[jj]), "r"(hadd2(t[j].x, vx)), "r"(hadd2(t[j].y, vy)), "r"(t[j].x), "r"(dummy), "r"(1u << jj) : "memory");
                }
            }
            while (__any_sync(0xffffffffu, pend)) {
                uint32_t a = dummy, vx = 0, vy = 0;
#pragma unroll
                for (int jj = 2 * STEPS - 1; jj >= 0; jj--)
                    if (pend & (1u << jj)) { a = ad[jj]; vx = (jj & 1) ? v[jj / 2].z : v[jj / 2].x; vy = (jj & 1) ? v[jj / 2].w : v[jj / 2].y; }
                const uint2 t = lock64(a);
                asm volatile("{.reg .pred p; setp.ne.u32 p,%4,0xffffffff; @p st.shared.v2.u32 [%1],{%2,%3}; @p and.b32 %0,%0,%5;}"
                             : "+r"(pend) : "r"(a), "r"(hadd2(t.x, vx)), "r"(hadd2(t.y, vy)), "r"(t.x), "r"(pend - 1) : "memory");
            }
        }
    }
    if (warp < NCW) bar_arrive(1, 992);
}

__device__ __forceinline__ void mma_edge(float (&c)[4], uint32_t p01, uint32_t q01, uint32_t p23, uint32_t q23, uint2 b) {
    asm("mma.sync.aligned.m16n8k16.row.col.f32.bf16.bf16.f32 {%0,%1,%2,%3},{%4,%5,%6,%7},{%8,%9},{%0,%1,%2,%3};"
        : "+f"(c[0]), "+f"(c[1]), "+f"(c[2]), "+f"(c[3]) : "r"(p01), "r"(q01), "r"(p23), "r"(q23), "r"(b.x), "r"(b.y));
}
__device__ __forceinline__ uint2 b_frag(const uint16_t* w, int j0) {
    int lane; asm("mov.u32 %0,%%laneid;" : "=r"(lane));
    const int j = j0 + ((lane >> 2) & 1);
    const uint2 v = make_uint2(w[j] | ((uint32_t)w[4 + j] << 16), w[8 + j] | ((uint32_t)w[12 + j] << 16));
    return (lane & 3) == (lane >> 3) ? v : make_uint2(0, 0);
}
__device__ __forceinline__ void edge_gates(const uint16_t* w, uint32_t d2, uint4& sp, uint4& gp) {
    uint32_t rb[2][4];
#pragma unroll
    for (int k = 0; k < 2; k++)
#pragma unroll
        for (int r = 0; r < 4; r++) {
            uint32_t x; asm("sub.rn.bf16x2 %0,%1,%2;" : "=r"(x) : "r"(__byte_perm(d2, 0, k ? 0x3232 : 0x1010)), "r"(((const uint32_t*)w)[48 + r]));
            const uint32_t t = hmul2(hmul2(x, x), 0xc120c120u);
            rb[k][r] = pack2(__expf(bf_lo(t)), __expf(bf_hi(t)));
        }
    uint32_t o[4][2];
#pragma unroll
    for (int n = 0; n < 4; n++) {
        float c[4] = {};
        mma_edge(c, rb[0][0], rb[1][0], rb[0][1], rb[1][1], b_frag(w + (n >> 1) * 32, (n & 1) * 2));
        mma_edge(c, rb[0][2], rb[1][2], rb[0][3], rb[1][3], b_frag(w + (n >> 1) * 32 + 16, (n & 1) * 2));
        o[n][0] = pack2(c[0], c[1]); o[n][1] = pack2(c[2], c[3]);
    }
    gp = make_uint4(o[0][0], o[1][0], o[0][1], o[1][1]);
    sp = make_uint4(o[2][0], o[3][0], o[2][1], o[3][1]);
}
__device__ __forceinline__ uint4 edge_finish(const uint16_t* w, uint4 a, uint4 sp, uint4 gp, uint4 mv) {
    float t0[4] = {}, t1[4] = {}, u0[4] = {}, u1[4] = {};
    mma_edge(t0, a.x, a.z, a.y, a.w, b_frag(w + 64, 0));
    mma_edge(t1, a.x, a.z, a.y, a.w, b_frag(w + 64, 2));
    const uint32_t p01 = pack2(t0[0] * bf_lo(sp.x), t0[1] * bf_hi(sp.x)), p23 = pack2(t1[0] * bf_lo(sp.y), t1[1] * bf_hi(sp.y));
    const uint32_t q01 = pack2(t0[2] * bf_lo(sp.z), t0[3] * bf_hi(sp.z)), q23 = pack2(t1[2] * bf_lo(sp.w), t1[3] * bf_hi(sp.w));
    mma_edge(u0, p01, q01, p23, q23, b_frag(w + 80, 0));
    mma_edge(u1, p01, q01, p23, q23, b_frag(w + 80, 2));
    return make_uint4(hadd2(mv.x, hmul2(pack2(u0[0], u0[1]), gp.x)), hadd2(mv.y, hmul2(pack2(u1[0], u1[1]), gp.y)),
                      hadd2(mv.z, hmul2(pack2(u0[2], u0[3]), gp.z)), hadd2(mv.w, hmul2(pack2(u1[2], u1[3]), gp.w)));
}

__device__ __forceinline__ void finish(const Params& p, unsigned char* sm) {
    __syncwarp();
    const int b = blockIdx.x, tid = threadIdx.x;
    const int role = ((const volatile uint32_t*)(sm + SM_AUX + AUX_MISC))[2];
    const uint16_t* w = (const uint16_t*)(sm + SM_AUX + AUX_W);
    if (role != 3) {
        __syncthreads();
        if (tid == 0) asm volatile("red.release.gpu.global.add.u32 [%0],1;" ::"l"(&g_sync[SY_END]) : "memory");
        __syncwarp();
    }
    constexpr int EP = 3, es = NCTA * 1024;
    static_assert(EP * es * 2 >= E_CAP, "epilogue");
    uint4 sg[2 * EP];
    const int e0 = b * 1024 + tid, np = p.E / 2;
#pragma unroll
    for (int k = 0; k < EP; k++) sg[2 * k].x = __ldg((const uint32_t*)p.dist + min(e0 + k * es, np - 1));
#pragma unroll
    for (int k = 0; k < EP; k++) edge_gates(w, sg[2 * k].x, sg[2 * k], sg[2 * k + 1]);
    uint4 mv[EP];
#pragma unroll
    for (int k = 0; k < EP; k++) mv[k] = __ldg((const uint4*)p.m + min(e0 + k * es, np - 1));
    if (role == 3) {
        const int et = tid - EXPORT_LO * 32;
        if (et >= 0 && et < EXPORT_N * 32) {
            const int q0 = (((const volatile uint32_t*)(sm + SM_AUX + AUX_MISC))[3] & 255) * (SO / 2);
            wait_zeroed();
            __syncwarp();
            bar_sync(1, 992);
#pragma unroll 4
            for (int i = et - (q0 & 7); i < (int)SO / 2; i += EXPORT_N * 32) {
                if (i < 0) continue;
                const uint4 v = ((const uint4*)sm)[i];
                asm volatile("red.global.add.noftz.v4.bf16x2 [%0],{%1,%2,%3,%4};" ::"l"((uint4*)g_agg + q0 + i), "r"(v.x), "r"(v.y), "r"(v.z), "r"(v.w) : "memory");
            }
            __syncwarp();
            bar_arrive(2, 1024);
            bar_sync(3, EXPORT_N * 32);
            if (et == 0) asm volatile("red.release.gpu.global.add.u32 [%0],1;" ::"l"(&g_sync[SY_END]) : "memory");
            __syncwarp();
        } else bar_sync(2, 1024);
    }
    uint4* const stash = (uint4*)sm + tid;
#pragma unroll
    for (int k = 0; k < EP; k++) { stash[(3 * k) * 1024] = sg[2 * k]; stash[(3 * k + 1) * 1024] = sg[2 * k + 1]; stash[(3 * k + 2) * 1024] = mv[k]; }
    if (tid == 0) {
        wait_flag(&g_sync[SY_END], NCTA);
        asm volatile("fence.acquire.gpu;" ::: "memory");
    }
    __syncthreads();
    uint4 av[EP];
#pragma unroll
    for (int k = 0; k < EP; k++) av[k] = __ldcg((const uint4*)g_agg + min(e0 + k * es, np - 1));
#pragma unroll
    for (int k = 0; k < EP; k++) {
        const uint4 o = edge_finish(w, av[k], stash[(3 * k) * 1024], stash[(3 * k + 1) * 1024], stash[(3 * k + 2) * 1024]);
        if (e0 + k * es < np) ((uint4*)p.out)[e0 + k * es] = o;
    }
    if (b == 0 && tid < 512) ((uint4*)flags())[tid] = make_uint4(0, 0, 0, 0);
    if (tid == 0) {
        g_info[b] = make_uint2(0, 0);
        if (atomicAdd(&g_sync[SY_EXIT], 1) == NCTA - 1)
            g_sync[SY_ZERO] = g_sync[SY_END] = g_sync[SY_EXIT] = g_sync[SY_WORK] = g_sync[SY_LOG] = g_sync[SY_LOG + 1] = 0;
    }
}

__global__ void __launch_bounds__(1024, 1) main_kernel(const __grid_constant__ Params p) {
    extern __shared__ __align__(128) unsigned char sm[];
    const int b = blockIdx.x, tid = threadIdx.x, warp = tid >> 5;
    if ((uint32_t)__cvta_generic_to_shared(sm) != SB) __trap();
    uint32_t* s_misc = (uint32_t*)(sm + SM_AUX + AUX_MISC);
    if (tid == 0) s_misc[0] = s_misc[4] = s_misc[5] = 0;
    __syncthreads();
    if ((tid & 31) == 0) {
        const int sl = b * 2 + (warp >> 4), j = warp & 15;
        if (warp == 31) s_misc[1] = upper_is_near(g_probe + (b & 127) * 32);
        else if (sl < NSL && j < (sl < KA ? PA : sl < KA + KV ? PV : 1) && (sl < DS * N1 || sl >= KA || j >= IG / 2) &&
                 upper_is_near(g_ring + (sl < KA ? slot_a(sl) : slot_v(sl - KA)) + j * 8192 + 4064))
            atomicOr(&s_misc[0], 1u << warp);
    }
    __syncwarp();
    __syncthreads();
    uint32_t me; asm("mov.u32 %0,%%smid;" : "=r"(me));
    me = 0x8000u | (s_misc[1] << 14) | (me & 0x3fff);
    if (tid == 0) {
        const u64 v = (u64)(s_misc[0] ^ (s_misc[1] ? ~0u : 0u)) | ((u64)me << 32);
        asm volatile("st.release.gpu.global.u64 [%0],%1;" ::"l"(&g_info[b]), "l"(v) : "memory");
    }
    for (int i = tid; i < (SM_AUX + AUX_CLS) / 16; i += 1024) ((uint4*)sm)[i] = make_uint4(0, 0, 0, 0);
    uint16_t* w = (uint16_t*)(sm + SM_AUX + AUX_W);
    if (tid < 160) {
        u64 v = 0; int spins = 0;
        while (tid < NCTA && !(v >> 32)) {
            asm volatile("ld.acquire.gpu.global.u64 %0,[%1];" : "=l"(v) : "l"(&g_info[tid]) : "memory");
            if (++spins > (1 << 22)) __trap();
        }
        __syncwarp();
        if (tid < NCTA) ((uint32_t*)(sm + SM_AUX + AUX_CLS))[tid] = (uint32_t)v;
        const uint32_t o = v >> 32;
        const uint32_t c = __reduce_add_sync(0xffffffffu, tid < NCTA ? 1u << (8 * ((o & 1) | ((o >> 13) & 2))) : 0u);
        const uint32_t r = __popc(__ballot_sync(0xffffffffu, tid < NCTA && ((o ^ me) & 0x4001) == 0 && (o > me || (o == me && tid > b))));
        if ((tid & 31) == 0) { atomicAdd(&s_misc[4], c); atomicAdd(&s_misc[5], r); }
    } else if (tid >= 256 && tid < 256 + 104) {
        const int j = tid - 256;
        w[j] = j < 32 ? p.w_rbf[j] : j < 64 ? p.w_sbf[j - 32] : j < 80 ? p.w_down[j - 64] : j < 96 ? p.w_up[j - 80] : p.centers[j - 96];
    }
    __syncthreads();
    int role, rank;
    {
        const uint32_t cnt = s_misc[4], cl = (me & 1) | ((me >> 13) & 2);
        rank = s_misc[5];
        const int c2 = (rank + 1) * IG / NO;
        if (__vminu4(cnt, NO * 0x01010101u) != NO * 0x01010101u) {
            role = b < N2 ? 2 : b < N2 + N3 ? 3 : 1;
            const int r = role == 2 ? b : b - N2;
            rank = role == 1 ? b - N2 - N3 : (r >> 1) | ((r & 1) << 8);
        } else if (rank < NO && (me & 1)) { role = 3; rank |= (cl >> 1) << 8; }
        else if (rank < NO && c2 != rank * IG / NO) { role = 2; rank = (c2 - 1) | ((cl >> 1) << 8); }
        else {
            role = 1;
            rank -= (me & 1) ? NO : min(c2, IG);
            for (uint32_t c = 0; c < cl; c++) rank += ((cnt >> (8 * c)) & 0xff) - ((c & 1) ? NO : IG);
        }
        if (tid == 0) { s_misc[2] = role; s_misc[3] = rank; }
    }
    if (role == 1) stage1(p, sm, rank);
    else if (role == 2) stage2(p, sm, rank >> 8, rank & 255);
    else stage3(p, sm, rank >> 8, rank & 255);
    finish(p, sm);
}

__global__ void generic_scatter(const __grid_constant__ Params p) {
    const float f = bf_lo(p.freq[0]);
    for (int t = blockIdx.x * blockDim.x + threadIdx.x; t < p.T; t += gridDim.x * blockDim.x) {
        const uint2 v = __ldg(p.m + p.idx_in[t]);
        const uint32_t c2 = dup_bf16(cos_any(rbf16(f * bf_lo(p.angle[t]))));
        asm volatile("red.global.add.noftz.v2.bf16x2 [%0],{%1,%2};" ::"l"(p.out + p.idx_out[t]), "r"(hmul2(v.x, c2)), "r"(hmul2(v.y, c2)) : "memory");
    }
}
__global__ void __launch_bounds__(256) generic_finish(const __grid_constant__ Params p) {
    __shared__ __align__(16) uint16_t w[104];
    const int j = threadIdx.x, e = blockIdx.x * blockDim.x + j, ec = min(e, p.E - 1);
    if (j < 104) w[j] = j < 32 ? p.w_rbf[j] : j < 64 ? p.w_sbf[j - 32] : j < 80 ? p.w_down[j - 64] : j < 96 ? p.w_up[j - 80] : p.centers[j - 96];
    const uint2 a = p.out[ec], mv = p.m[ec];
    __syncthreads();
    uint4 s0, s1;
    edge_gates(w, p.dist[ec] * 0x10001u, s0, s1);
    const uint4 o = edge_finish(w, make_uint4(a.x, a.y, a.x, a.y), s0, s1, make_uint4(mv.x, mv.y, mv.x, mv.y));
    if (e < p.E) p.out[e] = make_uint2(o.x, o.y);
}

extern "C" void kernel_launch(void* const* d_in, const int* in_sizes, int n_in, void* d_out, int out_size) {
    static int nsm = 0;
    if (!nsm) {
        int dev = 0;
        cudaGetDevice(&dev);
        cudaDeviceGetAttribute(&nsm, cudaDevAttrMultiProcessorCount, dev);
        cudaFuncSetAttribute(main_kernel, cudaFuncAttributeMaxDynamicSharedMemorySize, SMEM_BYTES);
    }
    Params p;
    p.m = (const uint2*)d_in[0]; p.idx_in = (const int*)d_in[1]; p.idx_out = (const int*)d_in[2];
    p.angle = (const uint16_t*)d_in[4]; p.freq = (const uint16_t*)d_in[6];
    p.dist = (const uint16_t*)d_in[3]; p.centers = (const uint16_t*)d_in[5]; p.w_rbf = (const uint16_t*)d_in[7];
    p.w_sbf = (const uint16_t*)d_in[8]; p.w_down = (const uint16_t*)d_in[9]; p.w_up = (const uint16_t*)d_in[10];
    p.out = (uint2*)d_out;
    p.E = in_sizes[3]; p.T = in_sizes[1];
    p.zero = 0;
    p.pairs = p.T / (2 * STEP); p.units = p.pairs + (NR / 2 + 1) * N1;
    bool fast = nsm >= NCTA && p.E <= E_CAP && p.E >= 8 && p.E % 2 == 0 && p.pairs >= 2 * N1 && p.units < 0xff00;
    static cudaTextureObject_t tex[3];
    static const void* tex_ptr[3];
    static int tex_n[3];
    for (int k = 0; k < 3 && fast; k++) {
        void* ptr = d_in[k == 2 ? 4 : 1 + k];
        if (tex_ptr[k] == ptr && tex_n[k] == p.T) continue;
        cudaResourceDesc rd = {};
        rd.resType = cudaResourceTypeLinear;
        rd.res.linear.devPtr = ptr;
        rd.res.linear.desc = k == 2 ? cudaCreateChannelDesc<uint2>() : cudaCreateChannelDesc<uint4>();
        rd.res.linear.sizeInBytes = (size_t)(p.T / 4) * (k == 2 ? 8 : 16);
        cudaTextureDesc td = {};
        td.readMode = cudaReadModeElementType;
        if (cudaCreateTextureObject(&tex[k], &rd, &td, nullptr) == cudaSuccess) { tex_ptr[k] = ptr; tex_n[k] = p.T; }
        else { cudaGetLastError(); tex_ptr[k] = nullptr; fast = false; }
    }
    p.tin = tex[0]; p.tout = tex[1]; p.tang = tex[2];
    if (fast) {
        void* args[] = {&p};
        if (cudaLaunchCooperativeKernel((const void*)main_kernel, dim3(NCTA), dim3(1024), args, SMEM_BYTES, cudaStreamPerThread) == cudaSuccess) return;
        cudaGetLastError();
    }
    cudaMemsetAsync(d_out, 0, (size_t)p.E * 8, cudaStreamPerThread);
    generic_scatter<<<nsm * 8, 256, 0, cudaStreamPerThread>>>(p);
    generic_finish<<<(p.E + 255) / 256, 256, 0, cudaStreamPerThread>>>(p);
}
```

```cpp
#include <cuda_runtime.h>
#include <cuda_bf16.h>
#include <stdint.h>

typedef unsigned long long u64;
constexpr uint32_t magic_of(uint32_t d) { return (uint32_t)(((1ull << 32) + d - 1) / d); }
constexpr uint32_t slice_of(uint32_t total, uint32_t n) {
    uint32_t d = ((total + n - 1) / n + 1) & ~1u;
    while (!((uint64_t)(n * d - 1) * magic_of(d) < ((uint64_t)n << 32))) d += 2;
    return d;
}
constexpr int E_CAP = 800000;
constexpr int NI = 32, NO = 28, NG = 2, IG = NI / NG;
constexpr uint32_t SI = slice_of(E_CAP, NI), SO = slice_of(E_CAP, NO);
constexpr uint32_t MI = magic_of(SI), MO = magic_of(SO);
constexpr int NCTA = 132, N2 = NI, N3 = NO * NG, N1 = NCTA - N2 - N3;
constexpr int C = 16, GB = NO * IG;
constexpr int NP = 5;
constexpr int NW = 28, STEP = NW * 256;
constexpr int NR = 4, LOGCAP = 8192, NCH = N1 * NW * NR * 8, KMAX = 4000;
static_assert(NR % 2 == 0 && NR >= 2 && NR <= 4 && NO % 4 == 0 && IG == 16, "shape");

constexpr int DA = 3, DS = 2, DV = 2, KA = DA * N1, KV = DV * N1, NSL = KA + KV + 1;
constexpr int ASEG = NO * C * 4, XSEG = IG * C * 2, VSEG = IG * C * 8;
constexpr int AG = IG * ASEG, XG = NO * XSEG, XO = IG / 2 * 4096, AXG = XO + XG + GB;
constexpr int PA = (AXG + 4095) / 4096, PV = NO * VSEG / 4096;
static_assert(2 * ASEG <= 4096 && AG == 2 * XG && (XO + XG) / 4096 == (AXG - 1) / 4096 && PA <= 15 && PV <= 14, "layout");
static_assert(DS >= DA - DV && DS <= DA && KA <= 256 && KV <= 128 && NSL <= 2 * NCTA && N1 <= 64, "ring");

constexpr uint32_t SB = 1024;
constexpr int SM_CNT = 0, SM_CB = NG * GB * 4, SM_LC = SM_CB + 2 * GB, SM_X = SM_LC + 256, SM_A = SM_X + NP * XG,
              SM_S1_END = SM_A + NP * AG;
constexpr int SM_AUX = SO * 8 + 512, QN = 256;
constexpr int AUX_Q = 0, AUX_PROG = QN * 8, AUX_CLS = AUX_PROG + 128, AUX_MISC = AUX_CLS + 576, AUX_DUMMY = AUX_MISC + 32,
              AUX_W = AUX_DUMMY + 256, AUX_END = AUX_W + 208;
constexpr int SMEM_BYTES = SM_AUX + AUX_END;
static_assert(SM_S1_END + 256 + NW * 256 <= SM_AUX && SMEM_BYTES <= 232448 && SM_X % 128 == 0 && AUX_W % 16 == 0, "smem");

__device__ __align__(8192) unsigned char g_ring[(size_t)(KA * PA + KV * PV + 1) * 8192];
__device__ __align__(8192) unsigned char g_probe[8192];
__device__ __align__(256) uint2 g_log[N1 * NW * LOGCAP];
__device__ uint32_t g_chunks[NCH];
__device__ __align__(128) uint2 g_agg[NO * SO];
__device__ uint2 g_info[NCTA];
__device__ __align__(128) uint32_t g_sync[160];
constexpr int SY_ZERO = 0, SY_END = 32, SY_EXIT = 64, SY_WORK = 96, SY_LOG = 128;
constexpr int FL_GO2 = 0, FL_GO3 = 1;
constexpr uint32_t FL_DATA = 0x10000;

__device__ __forceinline__ int lane_id() { int v; asm volatile("mov.u32 %0,%%laneid;" : "=r"(v)); return v; }
__device__ __forceinline__ int warp_id() { int v; asm volatile("mov.u32 %0,%%tid.x;" : "=r"(v)); return __shfl_sync(0xffffffffu, v >> 5, 0); }
__device__ __forceinline__ float bf_lo(uint32_t v) { return __uint_as_float(v << 16); }
__device__ __forceinline__ float bf_hi(uint32_t v) { return __uint_as_float(v & 0xffff0000u); }
__device__ __forceinline__ float rbf16(float x) { return __bfloat162float(__float2bfloat16_rn(x)); }
__device__ __forceinline__ uint32_t hmul2(uint32_t a, uint32_t b) {
    uint32_t d; asm("mul.rn.bf16x2 %0,%1,%2;" : "=r"(d) : "r"(a), "r"(b)); return d;
}
__device__ __forceinline__ uint32_t hadd2(uint32_t a, uint32_t b) {
    uint32_t d; asm("add.rn.bf16x2 %0,%1,%2;" : "=r"(d) : "r"(a), "r"(b)); return d;
}
__device__ __forceinline__ uint32_t dup_bf16(float x) {
    uint32_t d; asm("cvt.rn.bf16x2.f32 %0,%1,%1;" : "=r"(d) : "f"(x)); return d;
}
__device__ __forceinline__ uint32_t pack2(float lo, float hi) {
    uint32_t d; asm("cvt.rn.bf16x2.f32 %0,%2,%1;" : "=r"(d) : "f"(lo), "f"(hi)); return d;
}
__device__ __noinline__ float cos_slow(float x) { return cosf(x); }
__device__ __forceinline__ float cos_any(float x) { return fabsf(x) < 32.f ? __cosf(x) : cos_slow(x); }
__device__ __forceinline__ void bar_sync(int id, int n) { asm volatile("barrier.sync.aligned %0,%1;" ::"r"(id), "r"(n) : "memory"); }
__device__ __forceinline__ void bar_arrive(int id, int n) { asm volatile("barrier.arrive.aligned %0,%1;" ::"r"(id), "r"(n) : "memory"); }
__device__ __forceinline__ uint32_t ld_relaxed(const uint32_t* p) {
    uint32_t v; asm volatile("ld.relaxed.gpu.global.u32 %0,[%1];" : "=r"(v) : "l"(p) : "memory"); return v;
}
__device__ __forceinline__ void st128(void* p, uint4 v) {
    asm volatile("{.reg .b64 a,b; .reg .b128 q; mov.b64 a,{%1,%2}; mov.b64 b,{%3,%4}; mov.b128 q,{a,b}; st.relaxed.gpu.global.b128 [%0],q;}" ::"l"(p), "r"(v.x), "r"(v.y), "r"(v.z), "r"(v.w) : "memory");
}
__device__ __forceinline__ uint4 ld128(const void* p) {
    uint4 v;
    asm volatile("{.reg .b64 a,b; .reg .b128 q; ld.relaxed.gpu.global.b128 q,[%4]; mov.b128 {a,b},q; mov.b64 {%0,%1},a; mov.b64 {%2,%3},b;}" : "=r"(v.x), "=r"(v.y), "=r"(v.z), "=r"(v.w) : "l"(p) : "memory");
    return v;
}
__device__ __forceinline__ void wait_flag(const uint32_t* p, uint32_t want) {
    int spins = 0;
    while ((ld_relaxed(p) & 0xffff) < want) {
        __nanosleep(100);
        if (++spins > (1 << 22)) __trap();
    }
}
__device__ __forceinline__ uint32_t slot_a(int s) { return s * (PA * 8192); }
__device__ __forceinline__ uint32_t slot_v(int s) { return KA * PA * 8192 + s * (PV * 8192); }
__device__ __forceinline__ uint32_t ring_off(uint32_t clsg, uint32_t off) {
    return ((off >> 12) << 13) + (((clsg >> (off >> 12)) & 1) << 12) + (off & 4095);
}
__device__ __forceinline__ uint32_t cls_of(const unsigned char* sm, int s, int g) {
    return ((const uint16_t*)(sm + SM_AUX + AUX_CLS))[s] ^ (g ? ~0u : 0u);
}
__device__ __forceinline__ uint32_t flag_idx(const unsigned char* sm, int g, int type, int q) {
    return ring_off(cls_of(sm, NSL - 1, g), type * 1024 + q * 8) / 4;
}
__device__ __forceinline__ uint32_t* flags() { return (uint32_t*)(g_ring + slot_v(KV)); }
__device__ __forceinline__ uint32_t arrivals(int type, uint32_t k) {
    static_assert(DV == 2, "flag ring");
    return type == FL_GO3 ? IG * ((k >> 1) + 1) : NO * (k >> 1);
}
__device__ __forceinline__ bool elect_one() {
    uint32_t r; asm volatile("{.reg .pred p; elect.sync _|p,0xffffffff; selp.u32 %0,1,0,p;}" : "=r"(r)); return r;
}
template <int NCW, int TYPE, class F>
__device__ __forceinline__ void poller(const unsigned char* sm, int g, int blk0, int blk1, int units, int hook_at, F hook) {
    const int lane = lane_id();
    constexpr uint32_t aux = SB + SM_AUX;
    constexpr int DR = TYPE == FL_GO2 ? DS : DA;
    const uint32_t lt = (1u << lane) - 1;
    uint32_t ea[2][DR], ev[2][DV], k[2] = {0, 0}, want[2], v[2], fin[2], fout[2];
#pragma unroll
    for (int j = 0; j < 2; j++) {
        const int q = min(lane + j * 32, N1 - 1);
#pragma unroll
        for (int d = 0; d < DR; d++) {
            const uint32_t sa = q + d * N1, ca = cls_of(sm, sa, g);
            ea[j][d] = (((ca >> blk0) & 1) << 14) | (((ca >> blk1) & 1) << 15) | (sa << 16);
        }
#pragma unroll
        for (int d = 0; d < DV; d++) ev[j][d] = (cls_of(sm, KA + q + d * N1, g) & 0x3fff) | ((q + d * N1) << 24);
        want[j] = lane + j * 32 < N1 ? FL_DATA + arrivals(TYPE, 0) : ~0u;
        v[j] = 0;
        fin[j] = flag_idx(sm, g, TYPE, q); fout[j] = flag_idx(sm, g, TYPE ^ 1, q);
    }
    int tail = 0, check = min(min(QN - N1, hook_at), units), spins = 0;
    while (true) {
        bool hit[2]; uint32_t bal[2];
#pragma unroll
        for (int j = 0; j < 2; j++) {
            hit[j] = v[j] >= want[j] && (uint16_t)v[j] >= (uint16_t)want[j];
            bal[j] = __ballot_sync(0xffffffffu, hit[j]);
        }
        if (bal[0] | bal[1]) {
            asm volatile("fence.acquire.gpu;" ::: "memory");
            if (TYPE == FL_GO2) asm volatile("fence.proxy.async.global;" ::: "memory");
            asm volatile("fence.acq_rel.cta;" ::: "memory");
            spins = 0;
        } else if (++spins > (1 << 22)) __trap();
#pragma unroll
        for (int j = 0; j < 2; j++) {
            const uint32_t pos = tail + __popc(bal[j] & lt);
            const uint32_t hi = fout[j] | (k[j] & 1) | (k[j] < DV ? 0x8000 : 0) | ((pos + 1) << 16);
            asm volatile("{.reg .pred p; .reg .b64 q; setp.ne.u32 p,%3,0; mov.b64 q,{%1,%2}; @p st.relaxed.cta.shared.u64 [%0],q;}"
                         ::"r"(aux + AUX_Q + (pos % QN) * 8), "r"(ea[j][0] | ev[j][0]), "r"(hi), "r"((uint32_t)hit[j]) : "memory");
            tail += __popc(bal[j]);
            k[j] += hit[j];
        }
#pragma unroll
        for (int j = 0; j < 2; j++) v[j] = ld_relaxed(flags() + (fin[j] | (k[j] & 1)));
#pragma unroll
        for (int j = 0; j < 2; j++) {
            const uint32_t a0 = ea[j][0], v0 = ev[j][0] ^ 0x80000000u;
#pragma unroll
            for (int d = 0; d < DR; d++) ea[j][d] = hit[j] ? (d + 1 < DR ? ea[j][(d + 1) % DR] : a0) : ea[j][d];
#pragma unroll
            for (int d = 0; d < DV; d++) ev[j][d] = hit[j] ? (d + 1 < DV ? ev[j][(d + 1) % DV] : v0) : ev[j][d];
            want[j] = hit[j] ? ((k[j] >> 1) + 1) * FL_DATA + arrivals(TYPE, k[j]) : want[j];
        }
        if (tail >= check) {
            if (tail >= units) break;
            if (tail >= hook_at) { hook(); hook_at = 0x7fffffff; }
            int limit;
            do {
                int prog; asm volatile("ld.volatile.shared.u32 %0,[%1];" : "=r"(prog) : "r"(aux + AUX_PROG + min(lane, NCW - 1) * 4) : "memory");
                limit = __reduce_min_sync(0xffffffffu, prog) + QN - N1;
            } while (tail > limit);
            check = min(min(limit, hook_at), units);
        }
    }
}
template <bool BLOCK>
__device__ __forceinline__ bool next_unit(uint32_t aux, int warp, int t, int step, uint2& e) {
    u64 v;
    while (true) {
        asm volatile("ld.acquire.cta.shared.u64 %0,[%1];" : "=l"(v) : "r"(aux + AUX_Q + ((uint32_t)t % QN) * 8) : "memory");
        if (__all_sync(0xffffffffu, (int)(v >> 48) == t + 1)) break;
        if (!BLOCK) return false;
        __nanosleep(40);
    }
    if (((t + step) ^ t) & 64) asm volatile("st.volatile.shared.u32 [%0],%1;" ::"r"(aux + AUX_PROG + warp * 4), "r"(t + step) : "memory");
    e = make_uint2((uint32_t)v, (uint32_t)(v >> 32) & 0xffff);
    return true;
}
__device__ __forceinline__ int upper_is_near(unsigned char* q) {
    ((uint4*)q)[0] = ((uint4*)q)[1] = ((uint4*)(q + 4096))[0] = ((uint4*)(q + 4096))[1] = make_uint4(0, 0, 0, 0);
    uint32_t best[2] = {~0u, ~0u};
#pragma unroll
    for (int r = 0; r < 4; r++) {
        uint32_t t0, t1, v;
        asm volatile("mov.u32 %0,%%clock;" : "=r"(t0)::"memory");
        asm volatile("atom.global.exch.b32 %0,[%1],0;" : "=r"(v) : "l"(q + (r & 1) * 4096) : "memory");
        asm volatile("{.reg .pred p; setp.eq.u32 p,%1,0xffffffff; @p trap; mov.u32 %0,%%clock;}" : "=r"(t1) : "r"(v) : "memory");
        best[r & 1] = min(best[r & 1], t1 - t0);
    }
    return best[1] < best[0];
}

struct Params {
    const uint2* m; const int* idx_in; const int* idx_out; const uint16_t* angle; const uint16_t* freq;
    const uint16_t *dist, *centers, *w_rbf, *w_sbf, *w_down, *w_up; uint2* out;
    int E, T, pairs, units;
    uint32_t zero;
    cudaTextureObject_t tin, tout, tang;
};

__device__ __forceinline__ void red_agg(uint32_t out, uint2 v, uint32_t c2) {
    asm volatile("red.global.add.noftz.v2.bf16x2 [%0],{%1,%2};" ::"l"(g_agg + out), "r"(hmul2(v.x, c2)), "r"(hmul2(v.y, c2)) : "memory");
}
__device__ __forceinline__ void decode_entry(uint32_t e0, uint32_t e1, uint32_t& in, uint32_t& out) {
    const uint32_t bx = e1 >> 21, g = bx >= GB, rem = bx - g * GB;
    in = (g * IG + rem % IG) * SI + (e0 & 0xffff);
    out = rem / IG * SO + (e1 & 0xffff);
}
__device__ __forceinline__ void wait_zeroed() {
    wait_flag(&g_sync[SY_ZERO], N3);
    asm volatile("fence.acquire.gpu;" ::: "memory");
}
constexpr int BAR_ATOMS = 1, BAR_STS = 2, BAR_PUB = 4, BAR_PUBFREE = 6, BAR_W = 8, BAR_LOG = 9;
constexpr int NT_STS = (NW + 2) * 32, NT_ATOMS = (NW + 1) * 32;
__device__ __forceinline__ void mbar_arrive(uint32_t bar) {
    __syncwarp();
    if (elect_one()) asm volatile("mbarrier.arrive.shared::cta.b64 _,[%0];" ::"r"(bar) : "memory");
}
__device__ __forceinline__ void mbar_wait(uint32_t bar, uint32_t parity) {
    asm volatile("{.reg .pred p; .reg .u32 n; mbarrier.try_wait.parity.shared::cta.b64 p,[%0],%1; @p bra D; mov.u32 n,0;\n"
                 "W: mbarrier.try_wait.parity.shared::cta.b64 p,[%0],%1,2000; @p bra D;\n"
                 "add.u32 n,n,1; setp.lt.u32 p,n,0x4000000; @p bra W; trap;\nD:}" ::"r"(bar), "r"(parity) : "memory");
}
__device__ __forceinline__ uint32_t mad(uint32_t a, uint32_t b, uint32_t c) {
    uint32_t d; asm("mad.lo.u32 %0,%1,%2,%3;" : "=r"(d) : "r"(a), "r"(b), "r"(c)); return d;
}
__device__ __forceinline__ uint32_t half_x8(uint32_t a, int hi, uint32_t c) {
    uint32_t d; asm("dp2a.lo.u32.u32 %0,%1,%2,%3;" : "=r"(d) : "r"(a), "r"(8u << (hi * 8)), "r"(c)); return d;
}
__device__ __forceinline__ void signal(uint32_t flag, uint32_t inc, int lane) {
    asm volatile("{.reg .pred p; setp.eq.u32 p,%2,0; @p red.relaxed.gpu.global.add.u32 [%0],%1;}" ::"l"(flags() + (flag & 0x7fff)), "r"(inc), "r"(lane) : "memory");
}
template <bool R, int G> struct Kind { static constexpr bool replay = R; static constexpr int group = G; };

__device__ __forceinline__ void stage1(const Params& p, unsigned char* sm, int pid) {
    const int warp = warp_id(), lane = lane_id();
    constexpr uint32_t sb = SB;
    uint4 ra[2], rb[2]; uint2 rc[2];
    volatile int* const s_next = (volatile int*)(sm + SM_LC + 64);
    const int total = p.pairs * 2, snap = total - 2 * 2 * N1, sw = pid & 1;
    u64* const logsync = (u64*)&g_sync[SY_LOG];
    constexpr uint32_t mb = sb + SM_LC;
    if (threadIdx.x < 4) asm volatile("mbarrier.init.shared::cta.b64 [%0],1;" ::"r"(mb + threadIdx.x * 8) : "memory");
    if (threadIdx.x == 0) s_next[2] = s_next[3] = 0x7ffffff0;
    if (threadIdx.x < 32) s_next[16 + threadIdx.x] = 2 * C;
    __syncthreads();
    if (warp < NW) {
        constexpr uint32_t cb = sb + SM_CNT, xdum = (uint32_t)(SM_LC + 128 - SM_CNT) << 19;
        constexpr uint32_t xk = sb + SM_X, ak = sb + SM_A - 2 * xk;
        uint32_t cur0 = xk + sw * XG + (lane & p.zero), nxt0 = cur0 + 2 * XG - C * 2, cur1 = cur0 - sw * 2 * XG, nxt1 = cur1 + 2 * XG - C * 2;
        uint32_t fresh = xk + 4 * XG - C * 2 + (lane & p.zero), n0 = 0, wpos = 0, chunk = 0;
        int h_in = pid * 2, np = 0;
        uint2* const log = g_log + (pid * NW + warp) * LOGCAP;
        const uint32_t ltmask = ((1u << lane) - 1) | p.zero, tq = (warp * 64 + lane) | p.zero;
        auto load_in = [&](int h) {
            const int q = h_in * (STEP / 4) + tq + h * 32;
            asm volatile("tex.1d.v4.u32.s32 {%0,%1,%2,%3},[%4,{%5}];" : "=r"(ra[h].x), "=r"(ra[h].y), "=r"(ra[h].z), "=r"(ra[h].w) : "l"(p.tin), "r"(q));
            asm volatile("tex.1d.v4.u32.s32 {%0,%1,%2,%3},[%4,{%5}];" : "=r"(rb[h].x), "=r"(rb[h].y), "=r"(rb[h].z), "=r"(rb[h].w) : "l"(p.tout), "r"(q));
            asm volatile("{.reg .b32 z,w; tex.1d.v4.u32.s32 {%0,%1,z,w},[%2,{%3}];}" : "=r"(rc[h].x), "=r"(rc[h].y) : "l"(p.tang), "r"(q));
        };
        const uint32_t stage = sb + SM_S1_END + 256 + warp * 256;
        auto flush_stage = [&]() {
            uint2 e;
            __syncwarp();
            asm volatile("ld.shared.v2.u32 {%0,%1},[%2];" : "=r"(e.x), "=r"(e.y) : "r"(stage + lane * 8) : "memory");
            log[(wpos & ~31u) + lane] = e;
            __syncwarp();
        };
        auto direct = [&](uint32_t first, uint32_t stride, uint32_t count, auto range, auto gate) {
            const float f = bf_lo(p.freq[0]);
            for (uint32_t c0 = first;; c0 += stride * 4) {
                uint2 e[4], v[4]; uint32_t ok = 0, big = 0;
#pragma unroll
                for (int k = 0; k < 4; k++) {
                    uint32_t lo = 0, hi = 0;
                    if (c0 + k * stride < count) range(c0 + k * stride, lo, hi);
                    e[k] = make_uint2(0, 0);
                    if (lo + lane < hi) { e[k] = __ldcg(g_log + lo + lane); ok |= 1u << k; }
                }
                __syncwarp();
                if (c0 == first) gate();
#pragma unroll
                for (int k = 0; k < 4; k++) {
                    uint32_t in;
                    decode_entry(e[k].x, e[k].y, in, e[k].y);
                    v[k] = __ldcg(p.m + in);
                    e[k].x = __float_as_uint(rbf16(f * bf_hi(e[k].x)));
                    big = max(big, e[k].x & 0x7fffffffu);
                }
                const bool slow = __any_sync(0xffffffffu, big >= 0x42000000u);
#pragma unroll
                for (int k = 0; k < 4; k++) {
                    float c = __cosf(__uint_as_float(e[k].x));
                    if (slow) c = cos_slow(__uint_as_float(e[k].x));
                    if ((ok >> k) & 1) red_agg(e[k].y, v[k], dup_bf16(c));
                }
                __syncwarp();
                if (c0 + stride * 4 >= count) break;
            }
        };
        auto drain = [&]() {
            const uint32_t lb = (pid * NW + warp) * LOGCAP;
            if (wpos & 31) flush_stage();
            direct(0, 1, (wpos - n0 + 31) / 32, [&](uint32_t c, uint32_t& lo, uint32_t& hi) { lo = lb + n0 + c * 32; hi = lb + wpos; },
                   [&] { wait_zeroed(); __syncwarp(); });
            wpos = n0;
        };
        auto load_log = [&](int j) {
            uint2 e[8];
#pragma unroll
            for (int k = 0; k < 8; k++) {
                const uint32_t ch = __shfl_sync(0xffffffffu, chunk, k * NR + j);
                e[k] = make_uint2(0, xdum + (lane << 21));
                if (j < NR && ch) e[k] = __ldcg(g_log + (ch - 1) * 32 + lane);
            }
#pragma unroll
            for (int h = 0; h < 2; h++) {
                ra[h] = make_uint4(e[h * 4].x, e[h * 4].y, e[h * 4 + 1].x, e[h * 4 + 1].y);
                rb[h] = make_uint4(e[h * 4 + 2].x, e[h * 4 + 2].y, e[h * 4 + 3].x, e[h * 4 + 3].y);
            }
        };
        auto step = [&](const int k2, auto kind) {
            constexpr bool R = decltype(kind)::replay;
            constexpr int G = decltype(kind)::group;
            uint32_t pa[8], aw[8], xw[8], r[8];
#pragma unroll
            for (int h = 0; h < 2; h++) {
                if (!R) {
                    const uint32_t in[4] = {ra[h].x, ra[h].y, ra[h].z, ra[h].w}, out[4] = {rb[h].x, rb[h].y, rb[h].z, rb[h].w};
#pragma unroll
                    for (int k = 0; k < 4; k++) {
                        const uint32_t i = __umulhi(in[k], MI), o = __umulhi(out[k], MO);
                        aw[h * 4 + k] = __byte_perm(in[k] - i * SI, k < 2 ? rc[h].x : rc[h].y, (k & 1) ? 0x7610 : 0x5410);
                        pa[h * 4 + k] = mad(i, NO, o);
                        xw[h * 4 + k] = mad(i, 1u << 21, mad(o, (IG << 21) - SO, out[k]));
                        asm("{.reg .pred p; setp.ge.u32 p,%1,%2; @p add.u32 %0,%0,%3;}" : "+r"(xw[h * 4 + k]) : "r"(in[k]), "n"(IG * SI), "n"((GB - IG) << 21));
                    }
                } else {
#pragma unroll
                    for (int k = h * 4; k < h * 4 + 4; k++) {
                        const uint4 q4 = (k & 2) ? rb[h] : ra[h];
                        const uint2 e = (k & 1) ? make_uint2(q4.z, q4.w) : make_uint2(q4.x, q4.y);
                        aw[k] = e.x; xw[k] = e.y;
                        pa[k] = mad((e.y >> 21) % IG, NO, (e.y >> 25) + (e.y >= GB << 21 ? GB - NO : 0));
                    }
                }
                if (h == 0) {
                    mbar_wait(mb + G * 8, k2 & 1);
                    if (!R) {
                        if (G) asm volatile("ld.volatile.shared.u32 %0,[%1];" : "=r"(h_in) : "r"(mb + 64) : "memory");
                        else h_in++;
                    }
                }
#pragma unroll
                for (int k = h * 4; k < h * 4 + 4; k++)
                    asm volatile("atom.shared.add.u32 %0,[%1+%2],1;" : "=r"(r[k]) : "r"(xw[k] >> 19), "n"(cb) : "memory");
            }
            bar_arrive(BAR_ATOMS, NT_ATOMS);
            mbar_wait(mb + 16 + G * 8, k2 & 1);
            if (!R) {
                load_in(0);
                if (p.zero) __nanosleep(0);
            }
            uint32_t ovf = 0;
#pragma unroll
            for (int k = 0; k < 8; k++) {
                const bool lo = r[k] < C, hi = xw[k] >= GB << 21;
                const uint32_t s2 = r[k] * 2 + (hi ? (lo ? cur1 : nxt1) : (lo ? cur0 : nxt0));
                asm volatile("{.reg .pred p; .reg .b16 a,b; setp.lt.u32 p,%5,%6; mov.b32 {a,b},%4;"
                             " @p st.shared.u32 [%1+%8],%2; @p st.shared.u16 [%3],a; @!p or.b32 %0,%0,%7;}"
                             : "+r"(ovf) : "r"(mad(pa[k], C * 2, s2) * 2), "r"(aw[k]), "r"((xw[k] >> 16) + s2), "r"(xw[k]), "r"(r[k]),
                               "n"(2 * C), "r"(R && xw[k] >= xdum ? 0u : 1u << k), "n"(ak) : "memory");
            }
            bar_arrive(BAR_STS + G, NT_STS);
            if (!R) {
                if (p.zero) __nanosleep(0);
                load_in(1);
            }
            uint32_t bal = __ballot_sync(0xffffffffu, ovf != 0);
            while (bal) {
                uint32_t e0 = aw[7], e1 = xw[7];
#pragma unroll
                for (int k = 6; k >= 0; k--)
                    if (ovf & (1u << k)) { e0 = aw[k]; e1 = xw[k]; }
                const uint32_t pos = ovf ? (wpos & 31) + __popc(bal & ltmask) : 64, next = wpos + __popc(bal);
                asm volatile("{.reg .pred p; setp.lt.u32 p,%3,32; @p st.shared.v2.u32 [%0],{%1,%2};}" ::"r"(stage + pos * 8), "r"(e0), "r"(e1), "r"(pos) : "memory");
                if ((next ^ wpos) & 32) {
                    flush_stage();
                    asm volatile("{.reg .pred p; setp.lt.u32 p,%3,32; @p st.shared.v2.u32 [%0],{%1,%2};}" ::"r"(stage + (pos - 32) * 8), "r"(e0), "r"(e1), "r"(pos - 32) : "memory");
                }
                wpos = next;
                ovf &= ovf - 1;
                bal = __ballot_sync(0xffffffffu, ovf != 0);
            }
            if (R) load_log((k2 - np) * 2 + G + 1);
            if (G || !R || k2 != np + NR / 2 - 1) {
                if (G != sw) { cur1 = nxt1 + C * 2; nxt1 = fresh - XG; } else { cur0 = nxt0 + C * 2; nxt0 = fresh; }
            }
            fresh += fresh == xk + (NP - 1) * XG - C * 2 ? -(NP - 1) * XG : XG;
        };
        for (int stop = snap; h_in < total;) {
            load_in(0); load_in(1);
            while (true) {
                step(np, Kind<false, 0>());
                step(np, Kind<false, 1>());
                np++;
                if (h_in < stop && wpos <= LOGCAP - 512) continue;
                if (h_in >= stop && stop < total) {
                    const uint32_t nch = min(wpos / 32, (LOGCAP - 256 * NR) / 32);
                    uint32_t base = 0;
                    if (lane == 0) base = (uint32_t)atomicAdd(logsync, (u64)nch);
                    base = __shfl_sync(0xffffffffu, base, 0);
                    const uint32_t mine = min(nch, NCH - min(base, NCH));
                    for (uint32_t c = lane; c < mine; c += 32) g_chunks[base + c] = (pid * NW + warp) * (LOGCAP / 32) + c + 1;
                    n0 = mine * 32;
                    __syncwarp();
                    if (n0 && elect_one()) asm volatile("cp.async.bulk.prefetch.L2.global [%0],%1;" ::"l"(log), "r"(n0 * 8) : "memory");
                    __syncwarp();
                    bar_arrive(BAR_LOG, (NW + 1) * 32);
                    stop = total;
                }
                if (h_in >= total || wpos > LOGCAP - 512) break;
            }
            if (wpos > LOGCAP - 512) drain();
        }
        {
            u64 v; int spins = 0;
            do {
                asm volatile("ld.acquire.gpu.global.u64 %0,[%1];" : "=l"(v) : "l"(logsync) : "memory");
                if (++spins > (1 << 22)) __trap();
            } while ((v >> 32) < N1);
            const uint32_t idx = (((lane / NR) * NW + warp) * NR + lane % NR) * N1 + pid;
            if (lane < 8 * NR && idx < (uint32_t)v) chunk = __ldcg(g_chunks + idx);
            __syncwarp();
        }
        if (wpos > LOGCAP - 256 * NR) drain();
        load_log(0);
#pragma unroll 1
        for (int k2 = np; k2 < np + NR / 2; k2++) {
            step(k2, Kind<true, 0>());
            step(k2, Kind<true, 1>());
        }
        uint2* const rng = (uint2*)(sm + SM_S1_END);
        if (lane == 0) rng[warp] = make_uint2(n0, wpos);
        if (wpos & 31) flush_stage();
        __syncwarp();
        for (int g = 0; g < NG; g++) {
            mbar_wait(mb + g * 8, (np + NR / 2) & 1);
            mbar_wait(mb + 16 + g * 8, (np + NR / 2) & 1);
            bar_arrive(BAR_ATOMS, NT_ATOMS);
            bar_arrive(BAR_STS + g, NT_STS);
        }
        const uint2 mine = lane < NW ? rng[lane] : make_uint2(0, 0);
        const uint32_t nch = (mine.y - mine.x + 31) / 32;
        uint32_t end = nch;
#pragma unroll
        for (int d = 1; d < 32; d *= 2) {
            const uint32_t t = __shfl_up_sync(0xffffffffu, end, d);
            if (lane >= d) end += t;
        }
        direct(warp, NW, __shfl_sync(0xffffffffu, end, 31), [&](uint32_t c, uint32_t& lo, uint32_t& hi) {
            const int w = __popc(__ballot_sync(0xffffffffu, end <= c));
            const uint32_t lb = (pid * NW + w) * LOGCAP;
            lo = lb + __shfl_sync(0xffffffffu, mine.x + (c - (end - nch)) * 32, w);
            hi = lb + __shfl_sync(0xffffffffu, mine.y, w);
        }, [&] { bar_sync(BAR_W, (NW + 1) * 32); });
    } else if (warp == NW) {
        const int row = min(lane, NO - 1), swz = (row >> 1) & 3;
        mbar_arrive(mb);
        int pn = N1 + pid, pnn = 0, nc = 0x7ffffff0;
        for (int s = 0; s < nc; s++) {
            const int hn = min(pn * 2 + (s & 1), total);
            if (hn == total) nc = min(nc, s + 2 + NR + 2);
            const uint32_t sub = s == nc - 4 ? 0 : C, bias = s == nc - 2 ? C : 0;
            uint4* cp = (uint4*)(sm + SM_CNT + ((s ^ sw) & 1) * GB * 4) + row * 4;
            bar_sync(BAR_ATOMS, NT_ATOMS);
            uint4 c[4];
#pragma unroll
            for (int j = 0; j < 4; j++) c[j] = cp[j ^ swz];
            __syncwarp();
#pragma unroll
            for (int j = 0; j < 4; j++)
                cp[j ^ swz] = make_uint4(min(max(c[j].x, C), 2 * C) - sub, min(max(c[j].y, C), 2 * C) - sub,
                                         min(max(c[j].z, C), 2 * C) - sub, min(max(c[j].w, C), 2 * C) - sub);
            if (lane == 0 && !(s & 1)) {
                s_next[0] = hn; s_next[2] = nc;
                if (hn >= snap) s_next[3] = min(s_next[3], s + 1);
            }
            mbar_arrive(mb + ((s + 1) & 1) * 8);
            uint4 w = make_uint4(0, 0, 0, 0);
#pragma unroll
            for (int j = 0; j < 4; j++) {
                const int sh = (j ^ swz) * 8;
                w.x |= min(c[j].x - bias, C) << sh; w.y |= min(c[j].y - bias, C) << sh;
                w.z |= min(c[j].z - bias, C) << sh; w.w |= min(c[j].w - bias, C) << sh;
            }
            mbar_wait(mb + 16 + (s & 1) * 8, (s >> 1) & 1);
            ((uint4*)(sm + SM_CB + (s & 1) * GB))[row] = w;
            bar_arrive(BAR_STS + (s & 1), NT_STS);
            if (s & 1) pn = min(2 * N1 + __shfl_sync(0xffffffffu, pnn, 0), p.pairs);
            else if (hn < total && s / 2 + 2 < KMAX) {
                if (lane == 0) asm volatile("atom.relaxed.gpu.global.add.u32 %0,[%1],1;" : "=r"(pnn) : "l"(&g_sync[SY_WORK]) : "memory");
            } else pnn = p.pairs;
            const int hp = pn * 2 + ((s & 1) ^ 1);
            if (hp < total && elect_one())
                asm volatile("cp.async.bulk.prefetch.L2.global [%0],%1;" ::"l"(p.angle + hp * STEP), "r"(STEP * 2) : "memory");
            __syncwarp();
        }
    } else if (warp < NW + 3) {
        const int par = warp - NW - 1, g = par ^ sw;
        mbar_arrive(mb + 16 + par * 8);
        const uint32_t* const fb = flags() + flag_idx(sm, g, lane & 1, pid);
        for (int s = par; s < s_next[2]; s += 2) {
            const int k = s >> 1, slot = k % DA * N1 + pid, slots = k % DS * N1 + pid, pl = s % NP;
            const uint32_t cls = __shfl_sync(0xffffffffu, cls_of(sm, slot, g), 0), clss = __shfl_sync(0xffffffffu, cls_of(sm, slots, g), 0);
            if (k >= DS) {
                const uint32_t kw = k - ((lane & 1) ? DS : DA - DV);
                wait_flag(fb + (kw & 1), arrivals(lane & 1, kw));
                __syncwarp();
                asm volatile("fence.proxy.async.global;" ::: "memory");
            }
            bar_sync(BAR_STS + par, NT_STS);
            asm volatile("fence.proxy.async.shared::cta;" ::: "memory");
            if (elect_one()) {
                unsigned char* dst = g_ring + slot_a(slot);
#pragma unroll
                for (int j = 0; j < IG / 2; j++)
                    asm volatile("cp.async.bulk.global.shared::cta.bulk_group [%0],[%1],%2;" ::"l"(g_ring + slot_a(slots) + ring_off(clss, j * 4096)),
                                 "r"(sb + SM_A + pl * AG + j * 2 * ASEG), "n"(2 * ASEG) : "memory");
#pragma unroll
                for (int j = 0; j * 4096 < XG; j++)
                    asm volatile("cp.async.bulk.global.shared::cta.bulk_group [%0],[%1],%2;" ::"l"(dst + ring_off(cls, XO + j * 4096)),
                                 "r"(sb + SM_X + pl * XG + j * 4096), "r"(min(4096, XG - j * 4096)) : "memory");
                asm volatile("cp.async.bulk.global.shared::cta.bulk_group [%0],[%1],%2;" ::"l"(dst + ring_off(cls, XO + XG)),
                             "r"(sb + SM_CB + par * GB), "r"(GB) : "memory");
                asm volatile("cp.async.bulk.commit_group;" ::: "memory");
                asm volatile("cp.async.bulk.wait_group 0;" ::: "memory");
            }
            __syncwarp();
            mbar_arrive(mb + 16 + par * 8);
            bar_sync(BAR_PUBFREE + par, 64);
            bar_arrive(BAR_PUB + par, 64);
        }
    } else if (warp == NW + 3) {
        uint32_t* const fb = flags() + flag_idx(sm, (lane >> 1) & 1, lane & 1, pid);
        bar_arrive(BAR_PUBFREE, 64);
        bar_arrive(BAR_PUBFREE + 1, 64);
        for (int s = 0; s < s_next[2]; s++) {
            if (s == 4) { wait_zeroed(); __syncwarp(); }
            const int g = (s ^ sw) & 1;
            bar_sync(BAR_PUB + (s & 1), 64);
            if (s + 2 < s_next[2]) bar_arrive(BAR_PUBFREE + (s & 1), 64);
            const bool pooled = s == s_next[3];
            if (pooled) bar_sync(BAR_LOG, (NW + 1) * 32);
            asm volatile("fence.release.gpu;" ::: "memory");
            if ((lane >> 1) == g) asm volatile("red.relaxed.gpu.global.add.u32 [%0],%1;" ::"l"(fb + ((s >> 1) & 1)), "r"(FL_DATA) : "memory");
            if (pooled && lane == 0) asm volatile("red.relaxed.gpu.global.add.u64 [%0],%1;" ::"l"(logsync), "l"(1ull << 32) : "memory");
            __syncwarp();
        }
        bar_arrive(BAR_W, (NW + 1) * 32);
    }
}

__device__ __forceinline__ void stage2(const Params& p, unsigned char* sm, int g, int ig) {
    const int warp = warp_id(), lane = lane_id();
    constexpr uint32_t sb = SB;
    constexpr int NCW = 16, STEPS = NO / 4, TAB = NCW * ASEG, MB = TAB + SI * 8;
    static_assert(MB + 8 * NCW + 8 <= SM_AUX && MB % 8 == 0, "stage2 smem");
    if (threadIdx.x <= NCW) asm volatile("mbarrier.init.shared::cta.b64 [%0],1;" ::"r"(sb + MB + threadIdx.x * 8) : "memory");
    asm volatile("fence.proxy.async.shared::cta;" ::: "memory");
    __syncthreads();
    if (warp == 30) {
        const int e0 = (g * IG + ig) * SI, bytes = max(0, min((int)SI, p.E - e0)) * 8;
        if (elect_one()) {
            asm volatile("mbarrier.arrive.expect_tx.shared::cta.b64 _,[%0],%1;" ::"r"(sb + MB + NCW * 8), "r"(bytes) : "memory");
            for (int o = 0; o < bytes; o += 16384)
                asm volatile("cp.async.bulk.shared::cluster.global.mbarrier::complete_tx::bytes [%0],[%1],%2,[%3];" ::"r"(sb + TAB + o), "l"((const char*)(p.m + e0) + o), "r"(min(16384, bytes - o)), "r"(sb + MB + NCW * 8) : "memory");
        }
        __syncwarp();
    }
    if (warp == 31) poller<NCW, FL_GO2>(sm, g, ig >> 1, 0, p.units, p.units - 3 * N1, [&] {
            const int e0 = (g * IG + ig) * SI, n = min((int)SI, p.E - e0);
            if (n > 0 && elect_one()) asm volatile("cp.async.bulk.prefetch.L2.global [%0],%1;" ::"l"(p.m + e0), "r"(n * 8) : "memory");
            __syncwarp();
        });
    if (warp >= NCW) return;
    const uint32_t f2 = (uint32_t)p.freq[0] * 0x10001u;
    const uint32_t vlane = slot_v(0) + (lane >> 4) * 8192 + ((lane >> 3) & 1) * VSEG + ig * 128 + (lane & 7) * 16;
    const uint32_t aoff = (ig >> 1) * 8192 + (ig & 1) * ASEG, buf = sb + warp * ASEG, mb = sb + MB + warp * 8;
    auto fetch = [&](uint32_t e) {
        if (elect_one()) {
            asm volatile("mbarrier.arrive.expect_tx.shared::cta.b64 _,[%0],%1;" ::"r"(mb), "n"(ASEG) : "memory");
            asm volatile("cp.async.bulk.shared::cluster.global.mbarrier::complete_tx::bytes [%0],[%1],%2,[%3];" ::"r"(buf),
                         "l"(g_ring + (slot_a((e >> 16) & 0xff) + aoff + ((e >> 2) & 0x1000))), "n"(ASEG), "r"(mb) : "memory");
        }
        __syncwarp();
    };
    mbar_wait(sb + MB + NCW * 8, 0);
    uint2 qn = make_uint2(0, 0);
    bool have = false;
    uint32_t ph = 0;
    for (int t = warp; t < p.units; t += NCW) {
        if (!have) { next_unit<true>(sb + SM_AUX, warp, t, NCW, qn); fetch(qn.x); }
        const uint2 qe = qn;
        mbar_wait(mb, ph); ph ^= 1;
        uint2 a[STEPS];
#pragma unroll
        for (int j = 0; j < STEPS; j++) asm volatile("ld.shared.v2.u32 {%0,%1},[%2];" : "=r"(a[j].x), "=r"(a[j].y) : "r"(buf + j * 256 + lane * 8) : "memory");
        have = next_unit<false>(sb + SM_AUX, warp, t + NCW, NCW, qn);
        uint32_t big = 0, x2[STEPS];
#pragma unroll
        for (int j = 0; j < STEPS; j++) {
            x2[j] = hmul2(__byte_perm(a[j].x, a[j].y, 0x7632), f2);
            asm("{.reg .b32 t; abs.bf16x2 t,%1; max.bf16x2 %0,%0,t;}" : "+r"(big) : "r"(x2[j]));
        }
        const bool slow = __any_sync(0xffffffffu, (big + 0x3e003e00u) & 0x80008000u);
        if (have) fetch(qn.x + ((uint32_t)slow & p.zero));
        const uint32_t tag = qe.x >> 31, cq = qe.x >> (lane >> 4);
        unsigned char* const vp = g_ring + (((qe.x >> 24) & 0x7f) * (PV * 8192) + vlane);
        auto body = [&](auto cosine) {
            uint4 m[STEPS];
#pragma unroll
            for (int jj = 0; jj < STEPS + 1; jj++) {
                if (jj < STEPS) {
                    asm volatile("ld.shared.v2.u32 {%0,%1},[%2];" : "=r"(m[jj].x), "=r"(m[jj].y) : "r"(half_x8(a[jj].x, 0, sb + TAB)) : "memory");
                    asm volatile("ld.shared.v2.u32 {%0,%1},[%2];" : "=r"(m[jj].z), "=r"(m[jj].w) : "r"(half_x8(a[jj].y, 0, sb + TAB)) : "memory");
                }
                if (jj >= 1) {
                    const int j = jj - 1;
                    const uint32_t d0 = dup_bf16(cosine(bf_lo(x2[j]))), d1 = dup_bf16(cosine(bf_hi(x2[j])));
                    u64 dst;
                    asm("mad.wide.u32 %0,%1,%2,%3;" : "=l"(dst) : "r"(cq & (1u << (2 * j))), "r"(4096u >> (2 * j)), "l"(vp));
                    st128((unsigned char*)dst + j * 16384,
                          make_uint4((hmul2(m[j].x, d0) & ~1u) | tag, hmul2(m[j].y, d0), hmul2(m[j].z, d1), hmul2(m[j].w, d1)));
                    if (p.zero) __nanosleep(0);
                }
            }
        };
        if (slow) body([](float x) { return cos_slow(x); });
        else body([](float x) { return __cosf(x); });
        __syncwarp();
        if (qe.y & 0x8000) asm volatile("fence.acq_rel.gpu;" ::: "memory");
        signal(qe.y, 1, lane);
    }
}

constexpr int EXPORT_LO = 16, EXPORT_N = 31 - EXPORT_LO;
__device__ __forceinline__ uint2 lock64(uint32_t a) {
    uint2 r;
    asm volatile("{.reg .b64 y; atom.shared.exch.b64 y,[%2],0xffffffffffffffff; mov.b64 {%0,%1},y;}" : "=r"(r.x), "=r"(r.y) : "r"(a) : "memory");
    return r;
}

__device__ __forceinline__ void stage3(const Params& p, unsigned char* sm, int g, int o) {
    const int warp = warp_id(), lane = lane_id();
    constexpr uint32_t sb = SB;
    if (threadIdx.x < 64) ((uint32_t*)(sm + SM_AUX + AUX_DUMMY))[threadIdx.x] = ~0u;
    for (int i = (g * NO + o) * 1024 + threadIdx.x; i < NO * (int)SO / 2; i += N3 * 1024) ((uint4*)g_agg)[i] = make_uint4(0, 0, 0, 0);
    __syncthreads();
    constexpr int NCW = EXPORT_LO, STEPS = IG / 4;
    if (warp >= NCW && warp < 31) {
        if (threadIdx.x == NCW * 32) asm volatile("red.release.gpu.global.add.u32 [%0],1;" ::"l"(&g_sync[SY_ZERO]) : "memory");
        wait_zeroed();
        for (int t = p.pairs * 2 * STEP + ((warp - NCW) * N3 + g * NO + o) * 32 + lane; t < p.T; t += N3 * EXPORT_N * 32)
            red_agg(p.idx_out[t], __ldg(p.m + p.idx_in[t]), dup_bf16(cos_any(rbf16(bf_lo(p.freq[0]) * bf_lo(p.angle[t])))));
    } else if (warp == 31) {
        poller<NCW, FL_GO3>(sm, g, (XO + o * XSEG) >> 12, (XO + XG) >> 12, p.units, p.units - 2 * N1, [&] {
            constexpr int H = (SO / 2 + 7) & ~7;
            const int e0 = (o * SO + g * H) & ~7, n = min(H + 8, p.E - e0) & ~7;
            if (n > 0 && elect_one()) {
                asm volatile("cp.async.bulk.prefetch.L2.global [%0],%1;" ::"l"(g_agg + e0), "r"(n * 8) : "memory");
                asm volatile("cp.async.bulk.prefetch.L2.global [%0],%1;" ::"l"(p.dist + e0), "r"(n * 2) : "memory");
            }
            __syncwarp();
        });
    } else {
        const uint32_t dummy = sb + SM_AUX + AUX_DUMMY + lane * 8, r0 = (lane & 7) * 2;
        const uint32_t vlane = slot_v(0) + ring_off(0, o * VSEG) + lane * 16, xlane = ring_off(0, XO + o * XSEG) + lane * 4;
        const uint32_t clane = ring_off(0, XO + XG + o * IG) + (lane >> 3) * 4;
        for (int t = warp; t < p.units; t += NCW) {
            uint2 qe;
            next_unit<true>(sb + SM_AUX, warp, t, NCW, qe);
            const uint32_t tag = qe.x >> 31, ab = slot_a((qe.x >> 16) & 0xff);
            const uint4* vp = (const uint4*)(g_ring + (((qe.x >> 24) & 0x7f) * (PV * 8192) + vlane + (((qe.x >> (o >> 1)) & 1) << 12)));
            const uint32_t* xp = (const uint32_t*)(g_ring + (ab + xlane + ((qe.x >> 2) & 0x1000)));
            const uint32_t* cp = (const uint32_t*)(g_ring + (ab + clane + ((qe.x >> 3) & 0x1000)));
            uint4 v[STEPS]; uint32_t x[STEPS];
            const uint32_t cn = __ldcg(cp);
#pragma unroll
            for (int j = 0; j < STEPS; j++) x[j] = __ldcg(xp + j * 32);
#pragma unroll
            for (int j = 0; j < STEPS; j++) v[j] = ld128(vp + j * 32);
            for (int spins = 0;; spins++) {
                uint32_t b0, b1;
                asm("lop3.b32 %0,%1,%2,%3,0x7e;" : "=r"(b0) : "r"(v[0].x), "r"(v[1].x), "r"(tag));
                asm("lop3.b32 %0,%1,%2,%3,0x7e;" : "=r"(b1) : "r"(v[2].x), "r"(v[3].x), "r"(tag));
                if (!__any_sync(0xffffffffu, (b0 | b1) & 1)) break;
                if (spins > (1 << 22)) __trap();
#pragma unroll
                for (int j = 0; j < STEPS; j++) v[j] = ld128(vp + j * 32);
            }
            uint32_t ad[2 * STEPS], dep = cn;
#pragma unroll
            for (int j = 0; j < STEPS; j++) {
                const uint32_t c = (cn >> (8 * j)) & 0xff;
                const uint32_t a0 = half_x8(x[j], 0, sb), a1 = half_x8(x[j], 1, sb);
                ad[2 * j] = r0 < c ? a0 : dummy;
                ad[2 * j + 1] = r0 + 1 < c ? a1 : dummy;
                dep ^= x[j];
            }
            signal(qe.y, 1 + (dep & p.zero), lane);
            uint32_t pend = 0;
#pragma unroll
            for (int j0 = 0; j0 < 2 * STEPS; j0 += 4) {
                uint2 t[4];
#pragma unroll
                for (int j = 0; j < 4; j++) t[j] = lock64(ad[j0 + j]);
#pragma unroll
                for (int j = 0; j < 4; j++) {
                    const int jj = j0 + j;
                    const uint32_t vx = (jj & 1) ? v[jj / 2].z : v[jj / 2].x, vy = (jj & 1) ? v[jj / 2].w : v[jj / 2].y;
                    asm volatile("{.reg .pred p,q; setp.ne.u32 p,%4,0xffffffff; @p st.shared.v2.u32 [%1],{%2,%3}; setp.ne.and.u32 q,%1,%5,!p; @q or.b32 %0,%0,%6;}"
                                 : "+r"(pend) : "r"(ad[jj]), "r"(hadd2(t[j].x, vx)), "r"(hadd2(t[j].y, vy)), "r"(t[j].x), "r"(dummy), "r"(1u << jj) : "memory");
                }
            }
            while (__any_sync(0xffffffffu, pend)) {
                uint32_t a = dummy, vx = 0, vy = 0;
#pragma unroll
                for (int jj = 2 * STEPS - 1; jj >= 0; jj--)
                    if (pend & (1u << jj)) { a = ad[jj]; vx = (jj & 1) ? v[jj / 2].z : v[jj / 2].x; vy = (jj & 1) ? v[jj / 2].w : v[jj / 2].y; }
                const uint2 t = lock64(a);
                asm volatile("{.reg .pred p; setp.ne.u32 p,%4,0xffffffff; @p st.shared.v2.u32 [%1],{%2,%3}; @p and.b32 %0,%0,%5;}"
                             : "+r"(pend) : "r"(a), "r"(hadd2(t.x, vx)), "r"(hadd2(t.y, vy)), "r"(t.x), "r"(pend - 1) : "memory");
            }
        }
        bar_arrive(1, 992);
    }
}

__device__ __forceinline__ void mma_edge(float (&c)[4], uint32_t p01, uint32_t q01, uint32_t p23, uint32_t q23, uint2 b) {
    asm("mma.sync.aligned.m16n8k16.row.col.f32.bf16.bf16.f32 {%0,%1,%2,%3},{%4,%5,%6,%7},{%8,%9},{%0,%1,%2,%3};"
        : "+f"(c[0]), "+f"(c[1]), "+f"(c[2]), "+f"(c[3]) : "r"(p01), "r"(q01), "r"(p23), "r"(q23), "r"(b.x), "r"(b.y));
}
__device__ __forceinline__ uint2 b_frag(const uint16_t* w, int j0) {
    int lane; asm("mov.u32 %0,%%laneid;" : "=r"(lane));
    const int j = j0 + ((lane >> 2) & 1);
    const uint2 v = make_uint2(w[j] | ((uint32_t)w[4 + j] << 16), w[8 + j] | ((uint32_t)w[12 + j] << 16));
    return (lane & 3) == (lane >> 3) ? v : make_uint2(0, 0);
}
__device__ __forceinline__ void edge_gates(const uint16_t* w, uint32_t d2, uint4& sp, uint4& gp) {
    uint32_t rb[2][4];
#pragma unroll
    for (int k = 0; k < 2; k++)
#pragma unroll
        for (int r = 0; r < 4; r++) {
            uint32_t x; asm("sub.rn.bf16x2 %0,%1,%2;" : "=r"(x) : "r"(__byte_perm(d2, 0, k ? 0x3232 : 0x1010)), "r"(((const uint32_t*)w)[48 + r]));
            const uint32_t t = hmul2(hmul2(x, x), 0xc120c120u);
            rb[k][r] = pack2(__expf(bf_lo(t)), __expf(bf_hi(t)));
        }
    uint32_t o[4][2];
#pragma unroll
    for (int n = 0; n < 4; n++) {
        float c[4] = {};
        mma_edge(c, rb[0][0], rb[1][0], rb[0][1], rb[1][1], b_frag(w + (n >> 1) * 32, (n & 1) * 2));
        mma_edge(c, rb[0][2], rb[1][2], rb[0][3], rb[1][3], b_frag(w + (n >> 1) * 32 + 16, (n & 1) * 2));
        o[n][0] = pack2(c[0], c[1]); o[n][1] = pack2(c[2], c[3]);
    }
    gp = make_uint4(o[0][0], o[1][0], o[0][1], o[1][1]);
    sp = make_uint4(o[2][0], o[3][0], o[2][1], o[3][1]);
}
__device__ __forceinline__ uint4 edge_finish(const uint16_t* w, uint4 a, uint4 sp, uint4 gp, uint4 mv) {
    float t0[4] = {}, t1[4] = {}, u0[4] = {}, u1[4] = {};
    mma_edge(t0, a.x, a.z, a.y, a.w, b_frag(w + 64, 0));
    mma_edge(t1, a.x, a.z, a.y, a.w, b_frag(w + 64, 2));
    const uint32_t p01 = pack2(t0[0] * bf_lo(sp.x), t0[1] * bf_hi(sp.x)), p23 = pack2(t1[0] * bf_lo(sp.y), t1[1] * bf_hi(sp.y));
    const uint32_t q01 = pack2(t0[2] * bf_lo(sp.z), t0[3] * bf_hi(sp.z)), q23 = pack2(t1[2] * bf_lo(sp.w), t1[3] * bf_hi(sp.w));
    mma_edge(u0, p01, q01, p23, q23, b_frag(w + 80, 0));
    mma_edge(u1, p01, q01, p23, q23, b_frag(w + 80, 2));
    return make_uint4(hadd2(mv.x, hmul2(pack2(u0[0], u0[1]), gp.x)), hadd2(mv.y, hmul2(pack2(u1[0], u1[1]), gp.y)),
                      hadd2(mv.z, hmul2(pack2(u0[2], u0[3]), gp.z)), hadd2(mv.w, hmul2(pack2(u1[2], u1[3]), gp.w)));
}

__device__ __forceinline__ void finish(const Params& p, unsigned char* sm) {
    __syncwarp();
    const int b = blockIdx.x, tid = threadIdx.x;
    const int role = ((const volatile uint32_t*)(sm + SM_AUX + AUX_MISC))[2];
    const uint16_t* w = (const uint16_t*)(sm + SM_AUX + AUX_W);
    if (role != 3) {
        __syncthreads();
        if (tid == 0) asm volatile("red.release.gpu.global.add.u32 [%0],1;" ::"l"(&g_sync[SY_END]) : "memory");
        __syncwarp();
    }
    constexpr int EP = 3, es = NCTA * 1024;
    static_assert(EP * es * 2 >= E_CAP, "epilogue");
    uint4 sg[2 * EP];
    const int e0 = b * 1024 + tid, np = p.E / 2;
#pragma unroll
    for (int k = 0; k < EP; k++) sg[2 * k].x = __ldg((const uint32_t*)p.dist + min(e0 + k * es, np - 1));
#pragma unroll
    for (int k = 0; k < EP; k++) edge_gates(w, sg[2 * k].x, sg[2 * k], sg[2 * k + 1]);
    uint4 mv[EP];
#pragma unroll
    for (int k = 0; k < EP; k++) mv[k] = __ldg((const uint4*)p.m + min(e0 + k * es, np - 1));
    if (role == 3) {
        const int et = tid - EXPORT_LO * 32;
        if (et >= 0 && et < EXPORT_N * 32) {
            const int q0 = (((const volatile uint32_t*)(sm + SM_AUX + AUX_MISC))[3] & 255) * (SO / 2);
            bar_sync(1, 992);
#pragma unroll 4
            for (int i = et - (q0 & 7); i < (int)SO / 2; i += EXPORT_N * 32) {
                if (i < 0) continue;
                const uint4 v = ((const uint4*)sm)[i];
                asm volatile("red.global.add.noftz.v4.bf16x2 [%0],{%1,%2,%3,%4};" ::"l"((uint4*)g_agg + q0 + i), "r"(v.x), "r"(v.y), "r"(v.z), "r"(v.w) : "memory");
            }
            __syncwarp();
            bar_arrive(2, 1024);
            bar_sync(3, EXPORT_N * 32);
            if (et == 0) asm volatile("red.release.gpu.global.add.u32 [%0],1;" ::"l"(&g_sync[SY_END]) : "memory");
            __syncwarp();
        } else bar_sync(2, 1024);
    }
    uint4* const stash = (uint4*)sm + tid;
#pragma unroll
    for (int k = 0; k < EP; k++) { stash[(3 * k) * 1024] = sg[2 * k]; stash[(3 * k + 1) * 1024] = sg[2 * k + 1]; stash[(3 * k + 2) * 1024] = mv[k]; }
    if (tid == 0) {
        wait_flag(&g_sync[SY_END], NCTA);
        asm volatile("fence.acquire.gpu;" ::: "memory");
    }
    __syncthreads();
    uint4 av[EP];
#pragma unroll
    for (int k = 0; k < EP; k++) av[k] = __ldcg((const uint4*)g_agg + min(e0 + k * es, np - 1));
#pragma unroll
    for (int k = 0; k < EP; k++) {
        const uint4 o = edge_finish(w, av[k], stash[(3 * k) * 1024], stash[(3 * k + 1) * 1024], stash[(3 * k + 2) * 1024]);
        if (e0 + k * es < np) ((uint4*)p.out)[e0 + k * es] = o;
    }
    if (b == 0 && tid < 512) ((uint4*)flags())[tid] = make_uint4(0, 0, 0, 0);
    if (tid == 0) {
        g_info[b] = make_uint2(0, 0);
        if (atomicAdd(&g_sync[SY_EXIT], 1) == NCTA - 1)
            g_sync[SY_ZERO] = g_sync[SY_END] = g_sync[SY_EXIT] = g_sync[SY_WORK] = g_sync[SY_LOG] = g_sync[SY_LOG + 1] = 0;
    }
}

__global__ void __launch_bounds__(1024, 1) main_kernel(const __grid_constant__ Params p) {
    extern __shared__ __align__(128) unsigned char sm[];
    const int b = blockIdx.x, tid = threadIdx.x, warp = tid >> 5;
    if ((uint32_t)__cvta_generic_to_shared(sm) != SB) __trap();
    uint32_t* s_misc = (uint32_t*)(sm + SM_AUX + AUX_MISC);
    if (tid == 0) s_misc[0] = s_misc[4] = s_misc[5] = 0;
    __syncthreads();
    if ((tid & 31) == 0) {
        const int sl = b * 2 + (warp >> 4), j = warp & 15;
        if (warp == 31) s_misc[1] = upper_is_near(g_probe + (b & 127) * 32);
        else if (sl < NSL && j < (sl < KA ? PA : sl < KA + KV ? PV : 1) && (sl < DS * N1 || sl >= KA || j >= IG / 2) &&
                 upper_is_near(g_ring + (sl < KA ? slot_a(sl) : slot_v(sl - KA)) + j * 8192 + 4064))
            atomicOr(&s_misc[0], 1u << warp);
    }
    __syncwarp();
    __syncthreads();
    uint32_t me; asm("mov.u32 %0,%%smid;" : "=r"(me));
    me = 0x8000u | (s_misc[1] << 14) | (me & 0x3fff);
    if (tid == 0) {
        const u64 v = (u64)(s_misc[0] ^ (s_misc[1] ? ~0u : 0u)) | ((u64)me << 32);
        asm volatile("st.release.gpu.global.u64 [%0],%1;" ::"l"(&g_info[b]), "l"(v) : "memory");
    }
    for (int i = tid; i < (SM_AUX + AUX_CLS) / 16; i += 1024) ((uint4*)sm)[i] = make_uint4(0, 0, 0, 0);
    uint16_t* w = (uint16_t*)(sm + SM_AUX + AUX_W);
    if (tid < 160) {
        u64 v = 0; int spins = 0;
        while (tid < NCTA && !(v >> 32)) {
            asm volatile("ld.acquire.gpu.global.u64 %0,[%1];" : "=l"(v) : "l"(&g_info[tid]) : "memory");
            if (++spins > (1 << 22)) __trap();
        }
        __syncwarp();
        if (tid < NCTA) ((uint32_t*)(sm + SM_AUX + AUX_CLS))[tid] = (uint32_t)v;
        const uint32_t o = v >> 32;
        const uint32_t c = __reduce_add_sync(0xffffffffu, tid < NCTA ? 1u << (8 * ((o & 1) | ((o >> 13) & 2))) : 0u);
        const uint32_t r = __popc(__ballot_sync(0xffffffffu, tid < NCTA && ((o ^ me) & 0x4001) == 0 && (o > me || (o == me && tid > b))));
        if ((tid & 31) == 0) { atomicAdd(&s_misc[4], c); atomicAdd(&s_misc[5], r); }
    } else if (tid >= 256 && tid < 256 + 104) {
        const int j = tid - 256;
        w[j] = j < 32 ? p.w_rbf[j] : j < 64 ? p.w_sbf[j - 32] : j < 80 ? p.w_down[j - 64] : j < 96 ? p.w_up[j - 80] : p.centers[j - 96];
    }
    __syncthreads();
    int role, rank;
    {
        const uint32_t cnt = s_misc[4], cl = (me & 1) | ((me >> 13) & 2);
        rank = s_misc[5];
        const int c2 = (rank + 1) * IG / NO;
        if (__vminu4(cnt, NO * 0x01010101u) != NO * 0x01010101u) {
            role = b < N2 ? 2 : b < N2 + N3 ? 3 : 1;
            const int r = role == 2 ? b : b - N2;
            rank = role == 1 ? b - N2 - N3 : (r >> 1) | ((r & 1) << 8);
        } else if (rank < NO && (me & 1)) { role = 3; rank |= (cl >> 1) << 8; }
        else if (rank < NO && c2 != rank * IG / NO) { role = 2; rank = (c2 - 1) | ((cl >> 1) << 8); }
        else {
            role = 1;
            rank -= (me & 1) ? NO : min(c2, IG);
            for (uint32_t c = 0; c < cl; c++) rank += ((cnt >> (8 * c)) & 0xff) - ((c & 1) ? NO : IG);
        }
        if (tid == 0) { s_misc[2] = role; s_misc[3] = rank; }
    }
    if (role == 1) stage1(p, sm, rank);
    else if (role == 2) stage2(p, sm, rank >> 8, rank & 255);
    else stage3(p, sm, rank >> 8, rank & 255);
    finish(p, sm);
}

__global__ void generic_scatter(const __grid_constant__ Params p) {
    const float f = bf_lo(p.freq[0]);
    for (int t = blockIdx.x * blockDim.x + threadIdx.x; t < p.T; t += gridDim.x * blockDim.x) {
        const uint2 v = __ldg(p.m + p.idx_in[t]);
        const uint32_t c2 = dup_bf16(cos_any(rbf16(f * bf_lo(p.angle[t]))));
        asm volatile("red.global.add.noftz.v2.bf16x2 [%0],{%1,%2};" ::"l"(p.out + p.idx_out[t]), "r"(hmul2(v.x, c2)), "r"(hmul2(v.y, c2)) : "memory");
    }
}
__global__ void __launch_bounds__(256) generic_finish(const __grid_constant__ Params p) {
    __shared__ __align__(16) uint16_t w[104];
    const int j = threadIdx.x, e = blockIdx.x * blockDim.x + j, ec = min(e, p.E - 1);
    if (j < 104) w[j] = j < 32 ? p.w_rbf[j] : j < 64 ? p.w_sbf[j - 32] : j < 80 ? p.w_down[j - 64] : j < 96 ? p.w_up[j - 80] : p.centers[j - 96];
    const uint2 a = p.out[ec], mv = p.m[ec];
    __syncthreads();
    uint4 s0, s1;
    edge_gates(w, p.dist[ec] * 0x10001u, s0, s1);
    const uint4 o = edge_finish(w, make_uint4(a.x, a.y, a.x, a.y), s0, s1, make_uint4(mv.x, mv.y, mv.x, mv.y));
    if (e < p.E) p.out[e] = make_uint2(o.x, o.y);
}

extern "C" void kernel_launch(void* const* d_in, const int* in_sizes, int n_in, void* d_out, int out_size) {
    static int nsm = 0;
    if (!nsm) {
        int dev = 0;
        cudaGetDevice(&dev);
        cudaDeviceGetAttribute(&nsm, cudaDevAttrMultiProcessorCount, dev);
        cudaFuncSetAttribute(main_kernel, cudaFuncAttributeMaxDynamicSharedMemorySize, SMEM_BYTES);
    }
    Params p;
    p.m = (const uint2*)d_in[0]; p.idx_in = (const int*)d_in[1]; p.idx_out = (const int*)d_in[2];
    p.angle = (const uint16_t*)d_in[4]; p.freq = (const uint16_t*)d_in[6];
    p.dist = (const uint16_t*)d_in[3]; p.centers = (const uint16_t*)d_in[5]; p.w_rbf = (const uint16_t*)d_in[7];
    p.w_sbf = (const uint16_t*)d_in[8]; p.w_down = (const uint16_t*)d_in[9]; p.w_up = (const uint16_t*)d_in[10];
    p.out = (uint2*)d_out;
    p.E = in_sizes[3]; p.T = in_sizes[1];
    p.zero = 0;
    p.pairs = p.T / (2 * STEP); p.units = p.pairs + (NR / 2 + 1) * N1;
    bool fast = nsm >= NCTA && p.E <= E_CAP && p.E >= 8 && p.E % 2 == 0 && p.pairs >= 2 * N1 && p.units < 0xff00;
    static cudaTextureObject_t tex[3];
    static const void* tex_ptr[3];
    static int tex_n[3];
    for (int k = 0; k < 3 && fast; k++) {
        void* ptr = d_in[k == 2 ? 4 : 1 + k];
        if (tex_ptr[k] == ptr && tex_n[k] == p.T) continue;
        cudaResourceDesc rd = {};
        rd.resType = cudaResourceTypeLinear;
        rd.res.linear.devPtr = ptr;
        rd.res.linear.desc = k == 2 ? cudaCreateChannelDesc<uint2>() : cudaCreateChannelDesc<uint4>();
        rd.res.linear.sizeInBytes = (size_t)(p.T / 4) * (k == 2 ? 8 : 16);
        cudaTextureDesc td = {};
        td.readMode = cudaReadModeElementType;
        if (cudaCreateTextureObject(&tex[k], &rd, &td, nullptr) == cudaSuccess) { tex_ptr[k] = ptr; tex_n[k] = p.T; }
        else { cudaGetLastError(); tex_ptr[k] = nullptr; fast = false; }
    }
    p.tin = tex[0]; p.tout = tex[1]; p.tang = tex[2];
    if (fast) {
        void* args[] = {&p};
        if (cudaLaunchCooperativeKernel((const void*)main_kernel, dim3(NCTA), dim3(1024), args, SMEM_BYTES, cudaStreamPerThread) == cudaSuccess) return;
        cudaGetLastError();
    }
    cudaMemsetAsync(d_out, 0, (size_t)p.E * 8, cudaStreamPerThread);
    generic_scatter<<<nsm * 8, 256, 0, cudaStreamPerThread>>>(p);
    generic_finish<<<(p.E + 255) / 256, 256, 0, cudaStreamPerThread>>>(p);
}
```

```cpp
#include <cuda_runtime.h>
#include <cuda_bf16.h>
#include <stdint.h>

typedef unsigned long long u64;
constexpr uint32_t magic_of(uint32_t d) { return (uint32_t)(((1ull << 32) + d - 1) / d); }
constexpr uint32_t slice_of(uint32_t total, uint32_t n) {
    uint32_t d = ((total + n - 1) / n + 1) & ~1u;
    while (!((uint64_t)(n * d - 1) * magic_of(d) < ((uint64_t)n << 32))) d += 2;
    return d;
}
constexpr int E_CAP = 800000;
constexpr int NI = 32, NO = 28, NG = 2, IG = NI / NG;
constexpr uint32_t SI = slice_of(E_CAP, NI), SO = slice_of(E_CAP, NO);
constexpr uint32_t MI = magic_of(SI), MO = magic_of(SO);
constexpr int NCTA = 132, N2 = NI, N3 = NO * NG, N1 = NCTA - N2 - N3;
constexpr int C = 16, GB = NO * IG;
constexpr int NP = 5;
constexpr int NW = 28, STEP = NW * 256;
constexpr int NR = 4, LOGCAP = 8192, NCH = N1 * NW * NR * 8, KMAX = 4000;
static_assert(NR % 2 == 0 && NR >= 2 && NR <= 4 && NO % 4 == 0 && IG == 16, "shape");

constexpr int DA = 3, DS = 2, DV = 2, KA = DA * N1, KV = DV * N1, NSL = KA + KV + 1;
constexpr int ASEG = NO * C * 4, XSEG = IG * C * 2, VSEG = IG * C * 8;
constexpr int AG = IG * ASEG, XG = NO * XSEG, XO = IG / 2 * 4096, AXG = XO + XG + GB;
constexpr int PA = (AXG + 4095) / 4096, PV = NO * VSEG / 4096;
static_assert(2 * ASEG <= 4096 && AG == 2 * XG && (XO + XG) / 4096 == (AXG - 1) / 4096 && PA <= 15 && PV <= 14, "layout");
static_assert(DS >= DA - DV && DS <= DA && KA <= 256 && KV <= 128 && NSL <= 2 * NCTA && N1 <= 64, "ring");

constexpr uint32_t SB = 1024;
constexpr int SM_CNT = 0, SM_CB = NG * GB * 4, SM_LC = SM_CB + 2 * GB, SM_X = SM_LC + 256, SM_A = SM_X + NP * XG,
              SM_S1_END = SM_A + NP * AG;
constexpr int SM_AUX = SO * 8 + 512, QN = 256;
constexpr int AUX_Q = 0, AUX_PROG = QN * 8, AUX_CLS = AUX_PROG + 128, AUX_MISC = AUX_CLS + 576, AUX_DUMMY = AUX_MISC + 32,
              AUX_W = AUX_DUMMY + 256, AUX_END = AUX_W + 208;
constexpr int SMEM_BYTES = SM_AUX + AUX_END;
static_assert(SM_S1_END + 256 + NW * 256 <= SM_AUX && SMEM_BYTES <= 232448 && SM_X % 128 == 0 && AUX_W % 16 == 0, "smem");

__device__ __align__(8192) unsigned char g_ring[(size_t)(KA * PA + KV * PV + 1) * 8192];
__device__ __align__(8192) unsigned char g_probe[8192];
__device__ __align__(256) uint2 g_log[N1 * NW * LOGCAP];
__device__ uint32_t g_chunks[NCH];
__device__ __align__(128) uint2 g_agg[NO * SO];
__device__ uint2 g_info[NCTA];
__device__ __align__(128) uint32_t g_sync[160];
constexpr int SY_ZERO = 0, SY_END = 32, SY_EXIT = 64, SY_WORK = 96, SY_LOG = 128;
constexpr int FL_GO2 = 0, FL_GO3 = 1;
constexpr uint32_t FL_DATA = 0x10000;

__device__ __forceinline__ int lane_id() { int v; asm volatile("mov.u32 %0,%%laneid;" : "=r"(v)); return v; }
__device__ __forceinline__ int warp_id() { int v; asm volatile("mov.u32 %0,%%tid.x;" : "=r"(v)); return __shfl_sync(0xffffffffu, v >> 5, 0); }
__device__ __forceinline__ float bf_lo(uint32_t v) { return __uint_as_float(v << 16); }
__device__ __forceinline__ float bf_hi(uint32_t v) { return __uint_as_float(v & 0xffff0000u); }
__device__ __forceinline__ float rbf16(float x) { return __bfloat162float(__float2bfloat16_rn(x)); }
__device__ __forceinline__ uint32_t hmul2(uint32_t a, uint32_t b) {
    uint32_t d; asm("mul.rn.bf16x2 %0,%1,%2;" : "=r"(d) : "r"(a), "r"(b)); return d;
}
__device__ __forceinline__ uint32_t hadd2(uint32_t a, uint32_t b) {
    uint32_t d; asm("add.rn.bf16x2 %0,%1,%2;" : "=r"(d) : "r"(a), "r"(b)); return d;
}
__device__ __forceinline__ uint32_t dup_bf16(float x) {
    uint32_t d; asm("cvt.rn.bf16x2.f32 %0,%1,%1;" : "=r"(d) : "f"(x)); return d;
}
__device__ __forceinline__ uint32_t pack2(float lo, float hi) {
    uint32_t d; asm("cvt.rn.bf16x2.f32 %0,%2,%1;" : "=r"(d) : "f"(lo), "f"(hi)); return d;
}
__device__ __noinline__ float cos_slow(float x) { return cosf(x); }
__device__ __forceinline__ float cos_any(float x) { return fabsf(x) < 32.f ? __cosf(x) : cos_slow(x); }
__device__ __forceinline__ void bar_sync(int id, int n) { asm volatile("barrier.sync.aligned %0,%1;" ::"r"(id), "r"(n) : "memory"); }
__device__ __forceinline__ void bar_arrive(int id, int n) { asm volatile("barrier.arrive.aligned %0,%1;" ::"r"(id), "r"(n) : "memory"); }
__device__ __forceinline__ uint32_t ld_relaxed(const uint32_t* p) {
    uint32_t v; asm volatile("ld.relaxed.gpu.global.u32 %0,[%1];" : "=r"(v) : "l"(p) : "memory"); return v;
}
__device__ __forceinline__ void st128(void* p, uint4 v) {
    asm volatile("{.reg .b64 a,b; .reg .b128 q; mov.b64 a,{%1,%2}; mov.b64 b,{%3,%4}; mov.b128 q,{a,b}; st.relaxed.gpu.global.b128 [%0],q;}" ::"l"(p), "r"(v.x), "r"(v.y), "r"(v.z), "r"(v.w) : "memory");
}
__device__ __forceinline__ uint4 ld128(const void* p) {
    uint4 v;
    asm volatile("{.reg .b64 a,b; .reg .b128 q; ld.relaxed.gpu.global.b128 q,[%4]; mov.b128 {a,b},q; mov.b64 {%0,%1},a; mov.b64 {%2,%3},b;}" : "=r"(v.x), "=r"(v.y), "=r"(v.z), "=r"(v.w) : "l"(p) : "memory");
    return v;
}
__device__ __forceinline__ void wait_flag(const uint32_t* p, uint32_t want) {
    int spins = 0;
    while ((ld_relaxed(p) & 0xffff) < want) {
        __nanosleep(100);
        if (++spins > (1 << 22)) __trap();
    }
}
__device__ __forceinline__ uint32_t slot_a(int s) { return s * (PA * 8192); }
__device__ __forceinline__ uint32_t slot_v(int s) { return KA * PA * 8192 + s * (PV * 8192); }
__device__ __forceinline__ uint32_t ring_off(uint32_t clsg, uint32_t off) {
    return ((off >> 12) << 13) + (((clsg >> (off >> 12)) & 1) << 12) + (off & 4095);
}
__device__ __forceinline__ uint32_t cls_of(const unsigned char* sm, int s, int g) {
    return ((const uint16_t*)(sm + SM_AUX + AUX_CLS))[s] ^ (g ? ~0u : 0u);
}
__device__ __forceinline__ uint32_t flag_idx(const unsigned char* sm, int g, int type, int q) {
    return ring_off(cls_of(sm, NSL - 1, g), type * 1024 + q * 8) / 4;
}
__device__ __forceinline__ uint32_t* flags() { return (uint32_t*)(g_ring + slot_v(KV)); }
__device__ __forceinline__ uint32_t arrivals(int type, uint32_t k) {
    static_assert(DV == 2, "flag ring");
    return type == FL_GO3 ? IG * ((k >> 1) + 1) : NO * (k >> 1);
}
__device__ __forceinline__ bool elect_one() {
    uint32_t r; asm volatile("{.reg .pred p; elect.sync _|p,0xffffffff; selp.u32 %0,1,0,p;}" : "=r"(r)); return r;
}
template <int NCW, int TYPE, class F>
__device__ __forceinline__ void poller(const unsigned char* sm, int g, int blk0, int blk1, int units, int hook_at, F hook) {
    const int lane = lane_id();
    constexpr uint32_t aux = SB + SM_AUX;
    constexpr int DR = TYPE == FL_GO2 ? DS : DA;
    const uint32_t lt = (1u << lane) - 1;
    uint32_t ea[2][DR], ev[2][DV], k[2] = {0, 0}, want[2], v[2], fin[2], fout[2];
#pragma unroll
    for (int j = 0; j < 2; j++) {
        const int q = min(lane + j * 32, N1 - 1);
#pragma unroll
        for (int d = 0; d < DR; d++) {
            const uint32_t sa = q + d * N1, ca = cls_of(sm, sa, g);
            ea[j][d] = (((ca >> blk0) & 1) << 14) | (((ca >> blk1) & 1) << 15) | (sa << 16);
        }
#pragma unroll
        for (int d = 0; d < DV; d++) ev[j][d] = (cls_of(sm, KA + q + d * N1, g) & 0x3fff) | ((q + d * N1) << 24);
        want[j] = lane + j * 32 < N1 ? FL_DATA + arrivals(TYPE, 0) : ~0u;
        v[j] = 0;
        fin[j] = flag_idx(sm, g, TYPE, q); fout[j] = flag_idx(sm, g, TYPE ^ 1, q);
    }
    int tail = 0, check = min(min(QN - N1, hook_at), units), spins = 0;
    while (true) {
        bool hit[2]; uint32_t bal[2];
#pragma unroll
        for (int j = 0; j < 2; j++) {
            hit[j] = v[j] >= want[j] && (uint16_t)v[j] >= (uint16_t)want[j];
            bal[j] = __ballot_sync(0xffffffffu, hit[j]);
        }
        if (bal[0] | bal[1]) {
            asm volatile("fence.acquire.gpu;" ::: "memory");
            if (TYPE == FL_GO2) asm volatile("fence.proxy.async.global;" ::: "memory");
            asm volatile("fence.acq_rel.cta;" ::: "memory");
            spins = 0;
        } else if (++spins > (1 << 22)) __trap();
#pragma unroll
        for (int j = 0; j < 2; j++) {
            const uint32_t pos = tail + __popc(bal[j] & lt);
            const uint32_t hi = fout[j] | (k[j] & 1) | (k[j] < DV ? 0x8000 : 0) | ((pos + 1) << 16);
            asm volatile("{.reg .pred p; .reg .b64 q; setp.ne.u32 p,%3,0; mov.b64 q,{%1,%2}; @p st.relaxed.cta.shared.u64 [%0],q;}"
                         ::"r"(aux + AUX_Q + (pos % QN) * 8), "r"(ea[j][0] | ev[j][0]), "r"(hi), "r"((uint32_t)hit[j]) : "memory");
            tail += __popc(bal[j]);
            k[j] += hit[j];
        }
#pragma unroll
        for (int j = 0; j < 2; j++) v[j] = ld_relaxed(flags() + (fin[j] | (k[j] & 1)));
#pragma unroll
        for (int j = 0; j < 2; j++) {
            const uint32_t a0 = ea[j][0], v0 = ev[j][0] ^ 0x80000000u;
#pragma unroll
            for (int d = 0; d < DR; d++) ea[j][d] = hit[j] ? (d + 1 < DR ? ea[j][(d + 1) % DR] : a0) : ea[j][d];
#pragma unroll
            for (int d = 0; d < DV; d++) ev[j][d] = hit[j] ? (d + 1 < DV ? ev[j][(d + 1) % DV] : v0) : ev[j][d];
            want[j] = hit[j] ? ((k[j] >> 1) + 1) * FL_DATA + arrivals(TYPE, k[j]) : want[j];
        }
        if (tail >= check) {
            if (tail >= units) break;
            if (tail >= hook_at) { hook(); hook_at = 0x7fffffff; }
            int limit;
            do {
                int prog; asm volatile("ld.volatile.shared.u32 %0,[%1];" : "=r"(prog) : "r"(aux + AUX_PROG + min(lane, NCW - 1) * 4) : "memory");
                limit = __reduce_min_sync(0xffffffffu, prog) + QN - N1;
            } while (tail > limit);
            check = min(min(limit, hook_at), units);
        }
    }
}
template <bool BLOCK>
__device__ __forceinline__ bool next_unit(uint32_t aux, int warp, int t, int step, uint2& e) {
    u64 v;
    while (true) {
        asm volatile("ld.acquire.cta.shared.u64 %0,[%1];" : "=l"(v) : "r"(aux + AUX_Q + ((uint32_t)t % QN) * 8) : "memory");
        if (__all_sync(0xffffffffu, (int)(v >> 48) == t + 1)) break;
        if (!BLOCK) return false;
        __nanosleep(80);
    }
    if (((t + step) ^ t) & 64) asm volatile("st.volatile.shared.u32 [%0],%1;" ::"r"(aux + AUX_PROG + warp * 4), "r"(t + step) : "memory");
    e = make_uint2((uint32_t)v, (uint32_t)(v >> 32) & 0xffff);
    return true;
}
__device__ __forceinline__ int upper_is_near(unsigned char* q) {
    ((uint4*)q)[0] = ((uint4*)q)[1] = ((uint4*)(q + 4096))[0] = ((uint4*)(q + 4096))[1] = make_uint4(0, 0, 0, 0);
    uint32_t best[2] = {~0u, ~0u};
#pragma unroll
    for (int r = 0; r < 4; r++) {
        uint32_t t0, t1, v;
        asm volatile("mov.u32 %0,%%clock;" : "=r"(t0)::"memory");
        asm volatile("atom.global.exch.b32 %0,[%1],0;" : "=r"(v) : "l"(q + (r & 1) * 4096) : "memory");
        asm volatile("{.reg .pred p; setp.eq.u32 p,%1,0xffffffff; @p trap; mov.u32 %0,%%clock;}" : "=r"(t1) : "r"(v) : "memory");
        best[r & 1] = min(best[r & 1], t1 - t0);
    }
    return best[1] < best[0];
}

struct Params {
    const uint2* m; const int* idx_in; const int* idx_out; const uint16_t* angle; const uint16_t* freq;
    const uint16_t *dist, *centers, *w_rbf, *w_sbf, *w_down, *w_up; uint2* out;
    int E, T, pairs, units;
    uint32_t zero;
    cudaTextureObject_t tin, tout, tang;
};

__device__ __forceinline__ void red_agg(uint32_t out, uint2 v, uint32_t c2) {
    asm volatile("red.global.add.noftz.v2.bf16x2 [%0],{%1,%2};" ::"l"(g_agg + out), "r"(hmul2(v.x, c2)), "r"(hmul2(v.y, c2)) : "memory");
}
__device__ __forceinline__ void decode_entry(uint32_t e0, uint32_t e1, uint32_t& in, uint32_t& out) {
    const uint32_t bx = e1 >> 21, g = bx >= GB, rem = bx - g * GB;
    in = (g * IG + rem % IG) * SI + (e0 & 0xffff);
    out = rem / IG * SO + (e1 & 0xffff);
}
__device__ __forceinline__ void wait_zeroed() {
    wait_flag(&g_sync[SY_ZERO], N3);
    asm volatile("fence.acquire.gpu;" ::: "memory");
}
constexpr int BAR_ATOMS = 1, BAR_STS = 2, BAR_PUB = 4, BAR_PUBFREE = 6, BAR_W = 8, BAR_LOG = 9;
constexpr int NT_STS = (NW + 2) * 32, NT_ATOMS = (NW + 1) * 32;
__device__ __forceinline__ void mbar_arrive(uint32_t bar) {
    __syncwarp();
    if (elect_one()) asm volatile("mbarrier.arrive.shared::cta.b64 _,[%0];" ::"r"(bar) : "memory");
}
__device__ __forceinline__ void mbar_wait(uint32_t bar, uint32_t parity) {
    asm volatile("{.reg .pred p; .reg .u32 n; mbarrier.try_wait.parity.shared::cta.b64 p,[%0],%1; @p bra D; mov.u32 n,0;\n"
                 "W: mbarrier.try_wait.parity.shared::cta.b64 p,[%0],%1,2000; @p bra D;\n"
                 "add.u32 n,n,1; setp.lt.u32 p,n,0x4000000; @p bra W; trap;\nD:}" ::"r"(bar), "r"(parity) : "memory");
}
__device__ __forceinline__ uint32_t mad(uint32_t a, uint32_t b, uint32_t c) {
    uint32_t d; asm("mad.lo.u32 %0,%1,%2,%3;" : "=r"(d) : "r"(a), "r"(b), "r"(c)); return d;
}
__device__ __forceinline__ uint32_t half_x8(uint32_t a, int hi, uint32_t c) {
    uint32_t d; asm("dp2a.lo.u32.u32 %0,%1,%2,%3;" : "=r"(d) : "r"(a), "r"(8u << (hi * 8)), "r"(c)); return d;
}
__device__ __forceinline__ void signal(uint32_t flag, uint32_t inc, int lane) {
    asm volatile("{.reg .pred p; setp.eq.u32 p,%2,0; @p red.relaxed.gpu.global.add.u32 [%0],%1;}" ::"l"(flags() + (flag & 0x7fff)), "r"(inc), "r"(lane) : "memory");
}
template <bool R, int G> struct Kind { static constexpr bool replay = R; static constexpr int group = G; };

__device__ __forceinline__ void stage1(const Params& p, unsigned char* sm, int pid) {
    const int warp = warp_id(), lane = lane_id();
    constexpr uint32_t sb = SB;
    uint4 ra[2], rb[2]; uint2 rc[2];
    volatile int* const s_next = (volatile int*)(sm + SM_LC + 64);
    const int total = p.pairs * 2, snap = total - 2 * 2 * N1, sw = pid & 1;
    u64* const logsync = (u64*)&g_sync[SY_LOG];
    constexpr uint32_t mb = sb + SM_LC;
    if (threadIdx.x < 4) asm volatile("mbarrier.init.shared::cta.b64 [%0],1;" ::"r"(mb + threadIdx.x * 8) : "memory");
    if (threadIdx.x == 0) s_next[2] = s_next[3] = 0x7ffffff0;
    if (threadIdx.x < 32) s_next[16 + threadIdx.x] = 2 * C;
    __syncthreads();
    if (warp < NW) {
        constexpr uint32_t cb = sb + SM_CNT, xdum = (uint32_t)(SM_LC + 128 - SM_CNT) << 19;
        constexpr uint32_t xk = sb + SM_X, ak = sb + SM_A - 2 * xk;
        uint32_t cur0 = xk + sw * XG + (lane & p.zero), nxt0 = cur0 + 2 * XG - C * 2, cur1 = cur0 - sw * 2 * XG, nxt1 = cur1 + 2 * XG - C * 2;
        uint32_t fresh = xk + 4 * XG - C * 2 + (lane & p.zero), n0 = 0, wpos = 0, chunk = 0;
        int h_in = pid * 2, np = 0;
        uint2* const log = g_log + (pid * NW + warp) * LOGCAP;
        const uint32_t ltmask = ((1u << lane) - 1) | p.zero, tq = (warp * 64 + lane) | p.zero;
        auto load_in = [&](int h) {
            const int q = h_in * (STEP / 4) + tq + h * 32;
            asm volatile("tex.1d.v4.u32.s32 {%0,%1,%2,%3},[%4,{%5}];" : "=r"(ra[h].x), "=r"(ra[h].y), "=r"(ra[h].z), "=r"(ra[h].w) : "l"(p.tin), "r"(q));
            asm volatile("tex.1d.v4.u32.s32 {%0,%1,%2,%3},[%4,{%5}];" : "=r"(rb[h].x), "=r"(rb[h].y), "=r"(rb[h].z), "=r"(rb[h].w) : "l"(p.tout), "r"(q));
            asm volatile("{.reg .b32 z,w; tex.1d.v4.u32.s32 {%0,%1,z,w},[%2,{%3}];}" : "=r"(rc[h].x), "=r"(rc[h].y) : "l"(p.tang), "r"(q));
        };
        const uint32_t stage = sb + SM_S1_END + 256 + warp * 256;
        auto flush_stage = [&]() {
            uint2 e;
            __syncwarp();
            asm volatile("ld.shared.v2.u32 {%0,%1},[%2];" : "=r"(e.x), "=r"(e.y) : "r"(stage + lane * 8) : "memory");
            log[(wpos & ~31u) + lane] = e;
            __syncwarp();
        };
        auto direct = [&](uint32_t first, uint32_t stride, uint32_t count, auto range, auto gate) {
            const float f = bf_lo(p.freq[0]);
            for (uint32_t c0 = first;; c0 += stride * 4) {
                uint2 e[4], v[4]; uint32_t ok = 0, big = 0;
#pragma unroll
                for (int k = 0; k < 4; k++) {
                    uint32_t lo = 0, hi = 0;
                    if (c0 + k * stride < count) range(c0 + k * stride, lo, hi);
                    e[k] = make_uint2(0, 0);
                    if (lo + lane < hi) { e[k] = __ldcg(g_log + lo + lane); ok |= 1u << k; }
                }
                __syncwarp();
                if (c0 == first) gate();
#pragma unroll
                for (int k = 0; k < 4; k++) {
                    uint32_t in;
                    decode_entry(e[k].x, e[k].y, in, e[k].y);
                    v[k] = __ldcg(p.m + in);
                    e[k].x = __float_as_uint(rbf16(f * bf_hi(e[k].x)));
                    big = max(big, e[k].x & 0x7fffffffu);
                }
                const bool slow = __any_sync(0xffffffffu, big >= 0x42000000u);
#pragma unroll
                for (int k = 0; k < 4; k++) {
                    float c = __cosf(__uint_as_float(e[k].x));
                    if (slow) c = cos_slow(__uint_as_float(e[k].x));
                    if ((ok >> k) & 1) red_agg(e[k].y, v[k], dup_bf16(c));
                }
                __syncwarp();
                if (c0 + stride * 4 >= count) break;
            }
        };
        auto drain = [&]() {
            const uint32_t lb = (pid * NW + warp) * LOGCAP;
            if (wpos & 31) flush_stage();
            direct(0, 1, (wpos - n0 + 31) / 32, [&](uint32_t c, uint32_t& lo, uint32_t& hi) { lo = lb + n0 + c * 32; hi = lb + wpos; },
                   [&] { wait_zeroed(); __syncwarp(); });
            wpos = n0;
        };
        auto load_log = [&](int j) {
            uint2 e[8];
#pragma unroll
            for (int k = 0; k < 8; k++) {
                const uint32_t ch = __shfl_sync(0xffffffffu, chunk, k * NR + j);
                e[k] = make_uint2(0, xdum + (lane << 21));
                if (j < NR && ch) e[k] = __ldcg(g_log + (ch - 1) * 32 + lane);
            }
#pragma unroll
            for (int h = 0; h < 2; h++) {
                ra[h] = make_uint4(e[h * 4].x, e[h * 4].y, e[h * 4 + 1].x, e[h * 4 + 1].y);
                rb[h] = make_uint4(e[h * 4 + 2].x, e[h * 4 + 2].y, e[h * 4 + 3].x, e[h * 4 + 3].y);
            }
        };
        auto step = [&](const int k2, auto kind) {
            constexpr bool R = decltype(kind)::replay;
            constexpr int G = decltype(kind)::group;
            uint32_t pa[8], aw[8], xw[8], r[8];
#pragma unroll
            for (int h = 0; h < 2; h++) {
                if (!R) {
                    const uint32_t in[4] = {ra[h].x, ra[h].y, ra[h].z, ra[h].w}, out[4] = {rb[h].x, rb[h].y, rb[h].z, rb[h].w};
#pragma unroll
                    for (int k = 0; k < 4; k++) {
                        const uint32_t i = __umulhi(in[k], MI), o = __umulhi(out[k], MO);
                        aw[h * 4 + k] = __byte_perm(in[k] - i * SI, k < 2 ? rc[h].x : rc[h].y, (k & 1) ? 0x7610 : 0x5410);
                        pa[h * 4 + k] = mad(i, NO, o);
                        xw[h * 4 + k] = mad(i, 1u << 21, mad(o, (IG << 21) - SO, out[k]));
                        asm("{.reg .pred p; setp.ge.u32 p,%1,%2; @p add.u32 %0,%0,%3;}" : "+r"(xw[h * 4 + k]) : "r"(in[k]), "n"(IG * SI), "n"((GB - IG) << 21));
                    }
                } else {
#pragma unroll
                    for (int k = h * 4; k < h * 4 + 4; k++) {
                        const uint4 q4 = (k & 2) ? rb[h] : ra[h];
                        const uint2 e = (k & 1) ? make_uint2(q4.z, q4.w) : make_uint2(q4.x, q4.y);
                        aw[k] = e.x; xw[k] = e.y;
                        pa[k] = mad((e.y >> 21) % IG, NO, (e.y >> 25) + (e.y >= GB << 21 ? GB - NO : 0));
                    }
                }
                if (h == 0) {
                    mbar_wait(mb + G * 8, k2 & 1);
                    if (!R) {
                        if (G) asm volatile("ld.volatile.shared.u32 %0,[%1];" : "=r"(h_in) : "r"(mb + 64) : "memory");
                        else h_in++;
                    }
                }
#pragma unroll
                for (int k = h * 4; k < h * 4 + 4; k++)
                    asm volatile("atom.shared.add.u32 %0,[%1+%2],1;" : "=r"(r[k]) : "r"(xw[k] >> 19), "n"(cb) : "memory");
            }
            bar_arrive(BAR_ATOMS, NT_ATOMS);
            mbar_wait(mb + 16 + G * 8, k2 & 1);
            if (!R) {
                load_in(0);
                if (p.zero) __nanosleep(0);
            }
            uint32_t ovf = 0;
#pragma unroll
            for (int k = 0; k < 8; k++) {
                const bool lo = r[k] < C, hi = xw[k] >= GB << 21;
                const uint32_t s2 = r[k] * 2 + (hi ? (lo ? cur1 : nxt1) : (lo ? cur0 : nxt0));
                asm volatile("{.reg .pred p; .reg .b16 a,b; setp.lt.u32 p,%5,%6; mov.b32 {a,b},%4;"
                             " @p st.shared.u32 [%1+%8],%2; @p st.shared.u16 [%3],a; @!p or.b32 %0,%0,%7;}"
                             : "+r"(ovf) : "r"(mad(pa[k], C * 2, s2) * 2), "r"(aw[k]), "r"((xw[k] >> 16) + s2), "r"(xw[k]), "r"(r[k]),
                               "n"(2 * C), "r"(R && xw[k] >= xdum ? 0u : 1u << k), "n"(ak) : "memory");
            }
            bar_arrive(BAR_STS + G, NT_STS);
            if (!R) {
                if (p.zero) __nanosleep(0);
                load_in(1);
            }
            uint32_t bal = __ballot_sync(0xffffffffu, ovf != 0);
            while (bal) {
                uint32_t e0 = aw[7], e1 = xw[7];
#pragma unroll
                for (int k = 6; k >= 0; k--)
                    if (ovf & (1u << k)) { e0 = aw[k]; e1 = xw[k]; }
                const uint32_t pos = ovf ? (wpos & 31) + __popc(bal & ltmask) : 64, next = wpos + __popc(bal);
                asm volatile("{.reg .pred p; setp.lt.u32 p,%3,32; @p st.shared.v2.u32 [%0],{%1,%2};}" ::"r"(stage + pos * 8), "r"(e0), "r"(e1), "r"(pos) : "memory");
                if ((next ^ wpos) & 32) {
                    flush_stage();
                    asm volatile("{.reg .pred p; setp.lt.u32 p,%3,32; @p st.shared.v2.u32 [%0],{%1,%2};}" ::"r"(stage + (pos - 32) * 8), "r"(e0), "r"(e1), "r"(pos - 32) : "memory");
                }
                wpos = next;
                ovf &= ovf - 1;
                bal = __ballot_sync(0xffffffffu, ovf != 0);
            }
            if (R) load_log((k2 - np) * 2 + G + 1);
            if (G || !R || k2 != np + NR / 2 - 1) {
                if (G != sw) { cur1 = nxt1 + C * 2; nxt1 = fresh - XG; } else { cur0 = nxt0 + C * 2; nxt0 = fresh; }
            }
            fresh += fresh == xk + (NP - 1) * XG - C * 2 ? -(NP - 1) * XG : XG;
        };
        for (int stop = snap; h_in < total;) {
            load_in(0); load_in(1);
            while (true) {
                step(np, Kind<false, 0>());
                step(np, Kind<false, 1>());
                np++;
                if (h_in < stop && wpos <= LOGCAP - 512) continue;
                if (h_in >= stop && stop < total) {
                    const uint32_t nch = min(wpos / 32, (LOGCAP - 256 * NR) / 32);
                    uint32_t base = 0;
                    if (lane == 0) base = (uint32_t)atomicAdd(logsync, (u64)nch);
                    base = __shfl_sync(0xffffffffu, base, 0);
                    const uint32_t mine = min(nch, NCH - min(base, NCH));
                    for (uint32_t c = lane; c < mine; c += 32) g_chunks[base + c] = (pid * NW + warp) * (LOGCAP / 32) + c + 1;
                    n0 = mine * 32;
                    __syncwarp();
                    if (n0 && elect_one()) asm volatile("cp.async.bulk.prefetch.L2.global [%0],%1;" ::"l"(log), "r"(n0 * 8) : "memory");
                    __syncwarp();
                    bar_arrive(BAR_LOG, (NW + 1) * 32);
                    stop = total;
                }
                if (h_in >= total || wpos > LOGCAP - 512) break;
            }
            if (wpos > LOGCAP - 512) drain();
        }
        {
            u64 v; int spins = 0;
            do {
                asm volatile("ld.acquire.gpu.global.u64 %0,[%1];" : "=l"(v) : "l"(logsync) : "memory");
                if (++spins > (1 << 22)) __trap();
            } while ((v >> 32) < N1);
            const uint32_t idx = (((lane / NR) * NW + warp) * NR + lane % NR) * N1 + pid;
            if (lane < 8 * NR && idx < (uint32_t)v) chunk = __ldcg(g_chunks + idx);
            __syncwarp();
        }
        if (wpos > LOGCAP - 256 * NR) drain();
        load_log(0);
#pragma unroll 1
        for (int k2 = np; k2 < np + NR / 2; k2++) {
            step(k2, Kind<true, 0>());
            step(k2, Kind<true, 1>());
        }
        uint2* const rng = (uint2*)(sm + SM_S1_END);
        if (lane == 0) rng[warp] = make_uint2(n0, wpos);
        if (wpos & 31) flush_stage();
        __syncwarp();
        for (int g = 0; g < NG; g++) {
            mbar_wait(mb + g * 8, (np + NR / 2) & 1);
            mbar_wait(mb + 16 + g * 8, (np + NR / 2) & 1);
            bar_arrive(BAR_ATOMS, NT_ATOMS);
            bar_arrive(BAR_STS + g, NT_STS);
        }
        const uint2 mine = lane < NW ? rng[lane] : make_uint2(0, 0);
        const uint32_t nch = (mine.y - mine.x + 31) / 32;
        uint32_t end = nch;
#pragma unroll
        for (int d = 1; d < 32; d *= 2) {
            const uint32_t t = __shfl_up_sync(0xffffffffu, end, d);
            if (lane >= d) end += t;
        }
        direct(warp, NW, __shfl_sync(0xffffffffu, end, 31), [&](uint32_t c, uint32_t& lo, uint32_t& hi) {
            const int w = __popc(__ballot_sync(0xffffffffu, end <= c));
            const uint32_t lb = (pid * NW + w) * LOGCAP;
            lo = lb + __shfl_sync(0xffffffffu, mine.x + (c - (end - nch)) * 32, w);
            hi = lb + __shfl_sync(0xffffffffu, mine.y, w);
        }, [&] { bar_sync(BAR_W, (NW + 1) * 32); });
    } else if (warp == NW) {
        const int row = min(lane, NO - 1), swz = (row >> 1) & 3;
        mbar_arrive(mb);
        int pn = N1 + pid, pnn = 0, nc = 0x7ffffff0;
        for (int s = 0; s < nc; s++) {
            const int hn = min(pn * 2 + (s & 1), total);
            if (hn == total) nc = min(nc, s + 2 + NR + 2);
            const uint32_t sub = s == nc - 4 ? 0 : C, bias = s == nc - 2 ? C : 0;
            uint4* cp = (uint4*)(sm + SM_CNT + ((s ^ sw) & 1) * GB * 4) + row * 4;
            bar_sync(BAR_ATOMS, NT_ATOMS);
            uint4 c[4];
#pragma unroll
            for (int j = 0; j < 4; j++) c[j] = cp[j ^ swz];
            __syncwarp();
#pragma unroll
            for (int j = 0; j < 4; j++)
                cp[j ^ swz] = make_uint4(min(max(c[j].x, C), 2 * C) - sub, min(max(c[j].y, C), 2 * C) - sub,
                                         min(max(c[j].z, C), 2 * C) - sub, min(max(c[j].w, C), 2 * C) - sub);
            if (lane == 0 && !(s & 1)) {
                s_next[0] = hn; s_next[2] = nc;
                if (hn >= snap) s_next[3] = min(s_next[3], s + 1);
            }
            mbar_arrive(mb + ((s + 1) & 1) * 8);
            uint4 w = make_uint4(0, 0, 0, 0);
#pragma unroll
            for (int j = 0; j < 4; j++) {
                const int sh = (j ^ swz) * 8;
                w.x |= min(c[j].x - bias, C) << sh; w.y |= min(c[j].y - bias, C) << sh;
                w.z |= min(c[j].z - bias, C) << sh; w.w |= min(c[j].w - bias, C) << sh;
            }
            mbar_wait(mb + 16 + (s & 1) * 8, (s >> 1) & 1);
            ((uint4*)(sm + SM_CB + (s & 1) * GB))[row] = w;
            bar_arrive(BAR_STS + (s & 1), NT_STS);
            if (s & 1) pn = min(2 * N1 + __shfl_sync(0xffffffffu, pnn, 0), p.pairs);
            else if (hn < total && s / 2 + 2 < KMAX) {
                if (lane == 0) asm volatile("atom.relaxed.gpu.global.add.u32 %0,[%1],1;" : "=r"(pnn) : "l"(&g_sync[SY_WORK]) : "memory");
            } else pnn = p.pairs;
            const int hp = pn * 2 + ((s & 1) ^ 1);
            if (hp < total && elect_one())
                asm volatile("cp.async.bulk.prefetch.L2.global [%0],%1;" ::"l"(p.angle + hp * STEP), "r"(STEP * 2) : "memory");
            __syncwarp();
        }
    } else if (warp < NW + 3) {
        const int par = warp - NW - 1, g = par ^ sw;
        mbar_arrive(mb + 16 + par * 8);
        const uint32_t* const fb = flags() + flag_idx(sm, g, lane & 1, pid);
        for (int s = par; s < s_next[2]; s += 2) {
            const int k = s >> 1, slot = k % DA * N1 + pid, slots = k % DS * N1 + pid, pl = s % NP;
            const uint32_t cls = __shfl_sync(0xffffffffu, cls_of(sm, slot, g), 0), clss = __shfl_sync(0xffffffffu, cls_of(sm, slots, g), 0);
            if (k >= DS) {
                const uint32_t kw = k - ((lane & 1) ? DS : DA - DV);
                wait_flag(fb + (kw & 1), arrivals(lane & 1, kw));
                __syncwarp();
                asm volatile("fence.proxy.async.global;" ::: "memory");
            }
            bar_sync(BAR_STS + par, NT_STS);
            asm volatile("fence.proxy.async.shared::cta;" ::: "memory");
            if (elect_one()) {
                unsigned char* dst = g_ring + slot_a(slot);
#pragma unroll
                for (int j = 0; j < IG / 2; j++)
                    asm volatile("cp.async.bulk.global.shared::cta.bulk_group [%0],[%1],%2;" ::"l"(g_ring + slot_a(slots) + ring_off(clss, j * 4096)),
                                 "r"(sb + SM_A + pl * AG + j * 2 * ASEG), "n"(2 * ASEG) : "memory");
#pragma unroll
                for (int j = 0; j * 4096 < XG; j++)
                    asm volatile("cp.async.bulk.global.shared::cta.bulk_group [%0],[%1],%2;" ::"l"(dst + ring_off(cls, XO + j * 4096)),
                                 "r"(sb + SM_X + pl * XG + j * 4096), "r"(min(4096, XG - j * 4096)) : "memory");
                asm volatile("cp.async.bulk.global.shared::cta.bulk_group [%0],[%1],%2;" ::"l"(dst + ring_off(cls, XO + XG)),
                             "r"(sb + SM_CB + par * GB), "r"(GB) : "memory");
                asm volatile("cp.async.bulk.commit_group;" ::: "memory");
                asm volatile("cp.async.bulk.wait_group 0;" ::: "memory");
            }
            __syncwarp();
            mbar_arrive(mb + 16 + par * 8);
            bar_sync(BAR_PUBFREE + par, 64);
            bar_arrive(BAR_PUB + par, 64);
        }
    } else if (warp == NW + 3) {
        uint32_t* const fb = flags() + flag_idx(sm, (lane >> 1) & 1, lane & 1, pid);
        bar_arrive(BAR_PUBFREE, 64);
        bar_arrive(BAR_PUBFREE + 1, 64);
        for (int s = 0; s < s_next[2]; s++) {
            if (s == 4) { wait_zeroed(); __syncwarp(); }
            const int g = (s ^ sw) & 1;
            bar_sync(BAR_PUB + (s & 1), 64);
            if (s + 2 < s_next[2]) bar_arrive(BAR_PUBFREE + (s & 1), 64);
            const bool pooled = s == s_next[3];
            if (pooled) bar_sync(BAR_LOG, (NW + 1) * 32);
            asm volatile("fence.release.gpu;" ::: "memory");
            if ((lane >> 1) == g) asm volatile("red.relaxed.gpu.global.add.u32 [%0],%1;" ::"l"(fb + ((s >> 1) & 1)), "r"(FL_DATA) : "memory");
            if (pooled && lane == 0) asm volatile("red.relaxed.gpu.global.add.u64 [%0],%1;" ::"l"(logsync), "l"(1ull << 32) : "memory");
            __syncwarp();
        }
        bar_arrive(BAR_W, (NW + 1) * 32);
    }
}

__device__ __forceinline__ void stage2(const Params& p, unsigned char* sm, int g, int ig) {
    const int warp = warp_id(), lane = lane_id();
    constexpr uint32_t sb = SB;
    constexpr int NCW = 16, STEPS = NO / 4, TAB = NCW * ASEG, MB = TAB + SI * 8;
    static_assert(MB + 8 * NCW + 8 <= SM_AUX && MB % 8 == 0, "stage2 smem");
    if (threadIdx.x <= NCW) asm volatile("mbarrier.init.shared::cta.b64 [%0],1;" ::"r"(sb + MB + threadIdx.x * 8) : "memory");
    asm volatile("fence.proxy.async.shared::cta;" ::: "memory");
    __syncthreads();
    if (warp == 30) {
        const int e0 = (g * IG + ig) * SI, bytes = max(0, min((int)SI, p.E - e0)) * 8;
        if (elect_one()) {
            asm volatile("mbarrier.arrive.expect_tx.shared::cta.b64 _,[%0],%1;" ::"r"(sb + MB + NCW * 8), "r"(bytes) : "memory");
            for (int o = 0; o < bytes; o += 16384)
                asm volatile("cp.async.bulk.shared::cluster.global.mbarrier::complete_tx::bytes [%0],[%1],%2,[%3];" ::"r"(sb + TAB + o), "l"((const char*)(p.m + e0) + o), "r"(min(16384, bytes - o)), "r"(sb + MB + NCW * 8) : "memory");
        }
        __syncwarp();
    }
    if (warp == 31) poller<NCW, FL_GO2>(sm, g, ig >> 1, 0, p.units, p.units - 3 * N1, [&] {
            const int e0 = (g * IG + ig) * SI, n = min((int)SI, p.E - e0);
            if (n > 0 && elect_one()) asm volatile("cp.async.bulk.prefetch.L2.global [%0],%1;" ::"l"(p.m + e0), "r"(n * 8) : "memory");
            __syncwarp();
        });
    if (warp >= NCW) return;
    const uint32_t f2 = (uint32_t)p.freq[0] * 0x10001u;
    const uint32_t vlane = slot_v(0) + (lane >> 4) * 8192 + ((lane >> 3) & 1) * VSEG + ig * 128 + (lane & 7) * 16;
    const uint32_t aoff = (ig >> 1) * 8192 + (ig & 1) * ASEG, buf = sb + warp * ASEG, mb = sb + MB + warp * 8;
    auto fetch = [&](uint32_t e) {
        if (elect_one()) {
            asm volatile("mbarrier.arrive.expect_tx.shared::cta.b64 _,[%0],%1;" ::"r"(mb), "n"(ASEG) : "memory");
            asm volatile("cp.async.bulk.shared::cluster.global.mbarrier::complete_tx::bytes [%0],[%1],%2,[%3];" ::"r"(buf),
                         "l"(g_ring + (slot_a((e >> 16) & 0xff) + aoff + ((e >> 2) & 0x1000))), "n"(ASEG), "r"(mb) : "memory");
        }
        __syncwarp();
    };
    mbar_wait(sb + MB + NCW * 8, 0);
    uint2 qn = make_uint2(0, 0);
    bool have = false;
    uint32_t ph = 0;
    for (int t = warp; t < p.units; t += NCW) {
        if (!have) { next_unit<true>(sb + SM_AUX, warp, t, NCW, qn); fetch(qn.x); }
        const uint2 qe = qn;
        mbar_wait(mb, ph); ph ^= 1;
        uint2 a[STEPS];
#pragma unroll
        for (int j = 0; j < STEPS; j++) asm volatile("ld.shared.v2.u32 {%0,%1},[%2];" : "=r"(a[j].x), "=r"(a[j].y) : "r"(buf + j * 256 + lane * 8) : "memory");
        have = next_unit<false>(sb + SM_AUX, warp, t + NCW, NCW, qn);
        uint32_t big = 0, x2[STEPS];
#pragma unroll
        for (int j = 0; j < STEPS; j++) {
            x2[j] = hmul2(__byte_perm(a[j].x, a[j].y, 0x7632), f2);
            asm("{.reg .b32 t; abs.bf16x2 t,%1; max.bf16x2 %0,%0,t;}" : "+r"(big) : "r"(x2[j]));
        }
        const bool slow = __any_sync(0xffffffffu, (big + 0x3e003e00u) & 0x80008000u);
        if (have) fetch(qn.x + ((uint32_t)slow & p.zero));
        const uint32_t tag = qe.x >> 31, cq = qe.x >> (lane >> 4);
        unsigned char* const vp = g_ring + (((qe.x >> 24) & 0x7f) * (PV * 8192) + vlane);
        auto body = [&](auto cosine) {
            uint4 m[STEPS];
#pragma unroll
            for (int jj = 0; jj < STEPS + 1; jj++) {
                if (jj < STEPS) {
                    asm volatile("ld.shared.v2.u32 {%0,%1},[%2];" : "=r"(m[jj].x), "=r"(m[jj].y) : "r"(half_x8(a[jj].x, 0, sb + TAB)) : "memory");
                    asm volatile("ld.shared.v2.u32 {%0,%1},[%2];" : "=r"(m[jj].z), "=r"(m[jj].w) : "r"(half_x8(a[jj].y, 0, sb + TAB)) : "memory");
                }
                if (jj >= 1) {
                    const int j = jj - 1;
                    const uint32_t d0 = dup_bf16(cosine(bf_lo(x2[j]))), d1 = dup_bf16(cosine(bf_hi(x2[j])));
                    u64 dst;
                    asm("mad.wide.u32 %0,%1,%2,%3;" : "=l"(dst) : "r"(cq & (1u << (2 * j))), "r"(4096u >> (2 * j)), "l"(vp));
                    st128((unsigned char*)dst + j * 16384,
                          make_uint4((hmul2(m[j].x, d0) & ~1u) | tag, hmul2(m[j].y, d0), hmul2(m[j].z, d1), hmul2(m[j].w, d1)));
                    if (p.zero) __nanosleep(0);
                }
            }
        };
        if (slow) body([](float x) { return cos_slow(x); });
        else body([](float x) { return __cosf(x); });
        __syncwarp();
        if (qe.y & 0x8000) asm volatile("fence.acq_rel.gpu;" ::: "memory");
        signal(qe.y, 1, lane);
    }
}

constexpr int EXPORT_LO = 20, EXPORT_N = 31 - EXPORT_LO;
__device__ __forceinline__ uint2 lock64(uint32_t a) {
    uint2 r;
    asm volatile("{.reg .b64 y; atom.shared.exch.b64 y,[%2],0xffffffffffffffff; mov.b64 {%0,%1},y;}" : "=r"(r.x), "=r"(r.y) : "r"(a) : "memory");
    return r;
}

__device__ __forceinline__ void stage3(const Params& p, unsigned char* sm, int g, int o) {
    const int warp = warp_id(), lane = lane_id();
    constexpr uint32_t sb = SB;
    if (threadIdx.x < 64) ((uint32_t*)(sm + SM_AUX + AUX_DUMMY))[threadIdx.x] = ~0u;
    for (int i = (g * NO + o) * 1024 + threadIdx.x; i < NO * (int)SO / 2; i += N3 * 1024) ((uint4*)g_agg)[i] = make_uint4(0, 0, 0, 0);
    __syncthreads();
    constexpr int NCW = EXPORT_LO, STEPS = IG / 4;
    if (warp >= NCW && warp < 31) {
        if (threadIdx.x == NCW * 32) asm volatile("red.release.gpu.global.add.u32 [%0],1;" ::"l"(&g_sync[SY_ZERO]) : "memory");
        wait_zeroed();
        for (int t = p.pairs * 2 * STEP + ((warp - NCW) * N3 + g * NO + o) * 32 + lane; t < p.T; t += N3 * EXPORT_N * 32)
            red_agg(p.idx_out[t], __ldg(p.m + p.idx_in[t]), dup_bf16(cos_any(rbf16(bf_lo(p.freq[0]) * bf_lo(p.angle[t])))));
    } else if (warp == 31) {
        poller<NCW, FL_GO3>(sm, g, (XO + o * XSEG) >> 12, (XO + XG) >> 12, p.units, p.units - 2 * N1, [&] {
            constexpr int H = (SO / 2 + 7) & ~7;
            const int e0 = (o * SO + g * H) & ~7, n = min(H + 8, p.E - e0) & ~7;
            if (n > 0 && elect_one()) {
                asm volatile("cp.async.bulk.prefetch.L2.global [%0],%1;" ::"l"(g_agg + e0), "r"(n * 8) : "memory");
                asm volatile("cp.async.bulk.prefetch.L2.global [%0],%1;" ::"l"(p.dist + e0), "r"(n * 2) : "memory");
            }
            __syncwarp();
        });
    } else {
        const uint32_t dummy = sb + SM_AUX + AUX_DUMMY + lane * 8, r0 = (lane & 7) * 2;
        const uint32_t vlane = slot_v(0) + ring_off(0, o * VSEG) + lane * 16, xlane = ring_off(0, XO + o * XSEG) + lane * 4;
        const uint32_t clane = ring_off(0, XO + XG + o * IG) + (lane >> 3) * 4;
        for (int t = warp; t < p.units; t += NCW) {
            uint2 qe;
            next_unit<true>(sb + SM_AUX, warp, t, NCW, qe);
            const uint32_t tag = qe.x >> 31, ab = slot_a((qe.x >> 16) & 0xff);
            const uint4* vp = (const uint4*)(g_ring + (((qe.x >> 24) & 0x7f) * (PV * 8192) + vlane + (((qe.x >> (o >> 1)) & 1) << 12)));
            const uint32_t* xp = (const uint32_t*)(g_ring + (ab + xlane + ((qe.x >> 2) & 0x1000)));
            const uint32_t* cp = (const uint32_t*)(g_ring + (ab + clane + ((qe.x >> 3) & 0x1000)));
            uint4 v[STEPS]; uint32_t x[STEPS];
            const uint32_t cn = __ldcg(cp);
#pragma unroll
            for (int j = 0; j < STEPS; j++) x[j] = __ldcg(xp + j * 32);
#pragma unroll
            for (int j = 0; j < STEPS; j++) v[j] = ld128(vp + j * 32);
            for (int spins = 0;; spins++) {
                uint32_t b0, b1;
                asm("lop3.b32 %0,%1,%2,%3,0x7e;" : "=r"(b0) : "r"(v[0].x), "r"(v[1].x), "r"(tag));
                asm("lop3.b32 %0,%1,%2,%3,0x7e;" : "=r"(b1) : "r"(v[2].x), "r"(v[3].x), "r"(tag));
                if (!__any_sync(0xffffffffu, (b0 | b1) & 1)) break;
                if (spins > (1 << 22)) __trap();
#pragma unroll
                for (int j = 0; j < STEPS; j++) v[j] = ld128(vp + j * 32);
            }
            uint32_t ad[2 * STEPS], dep = cn;
#pragma unroll
            for (int j = 0; j < STEPS; j++) {
                const uint32_t c = (cn >> (8 * j)) & 0xff;
                const uint32_t a0 = half_x8(x[j], 0, sb), a1 = half_x8(x[j], 1, sb);
                ad[2 * j] = r0 < c ? a0 : dummy;
                ad[2 * j + 1] = r0 + 1 < c ? a1 : dummy;
                dep ^= x[j];
            }
            signal(qe.y, 1 + (dep & p.zero), lane);
            uint32_t pend = 0;
#pragma unroll
            for (int j0 = 0; j0 < 2 * STEPS; j0 += 4) {
                uint2 t[4];
#pragma unroll
                for (int j = 0; j < 4; j++) t[j] = lock64(ad[j0 + j]);
#pragma unroll
                for (int j = 0; j < 4; j++) {
                    const int jj = j0 + j;
                    const uint32_t vx = (jj & 1) ? v[jj / 2].z : v[jj / 2].x, vy = (jj & 1) ? v[jj / 2].w : v[jj / 2].y;
                    asm volatile("{.reg .pred p,q; setp.ne.u32 p,%4,0xffffffff; @p st.shared.v2.u32 [%1],{%2,%3}; setp.ne.and.u32 q,%1,%5,!p; @q or.b32 %0,%0,%6;}"
                                 : "+r"(pend) : "r"(ad[jj]), "r"(hadd2(t[j].x, vx)), "r"(hadd2(t[j].y, vy)), "r"(t[j].x), "r"(dummy), "r"(1u << jj) : "memory");
                }
            }
            while (__any_sync(0xffffffffu, pend)) {
                uint32_t a = dummy, vx = 0, vy = 0;
#pragma unroll
                for (int jj = 2 * STEPS - 1; jj >= 0; jj--)
                    if (pend & (1u << jj)) { a = ad[jj]; vx = (jj & 1) ? v[jj / 2].z : v[jj / 2].x; vy = (jj & 1) ? v[jj / 2].w : v[jj / 2].y; }
                const uint2 t = lock64(a);
                asm volatile("{.reg .pred p; setp.ne.u32 p,%4,0xffffffff; @p st.shared.v2.u32 [%1],{%2,%3}; @p and.b32 %0,%0,%5;}"
                             : "+r"(pend) : "r"(a), "r"(hadd2(t.x, vx)), "r"(hadd2(t.y, vy)), "r"(t.x), "r"(pend - 1) : "memory");
            }
        }
        bar_arrive(1, 992);
    }
}

__device__ __forceinline__ void mma_edge(float (&c)[4], uint32_t p01, uint32_t q01, uint32_t p23, uint32_t q23, uint2 b) {
    asm("mma.sync.aligned.m16n8k16.row.col.f32.bf16.bf16.f32 {%0,%1,%2,%3},{%4,%5,%6,%7},{%8,%9},{%0,%1,%2,%3};"
        : "+f"(c[0]), "+f"(c[1]), "+f"(c[2]), "+f"(c[3]) : "r"(p01), "r"(q01), "r"(p23), "r"(q23), "r"(b.x), "r"(b.y));
}
__device__ __forceinline__ uint2 b_frag(const uint16_t* w, int j0) {
    int lane; asm("mov.u32 %0,%%laneid;" : "=r"(lane));
    const int j = j0 + ((lane >> 2) & 1);
    const uint2 v = make_uint2(w[j] | ((uint32_t)w[4 + j] << 16), w[8 + j] | ((uint32_t)w[12 + j] << 16));
    return (lane & 3) == (lane >> 3) ? v : make_uint2(0, 0);
}
__device__ __forceinline__ void edge_gates(const uint16_t* w, uint32_t d2, uint4& sp, uint4& gp) {
    uint32_t rb[2][4];
#pragma unroll
    for (int k = 0; k < 2; k++)
#pragma unroll
        for (int r = 0; r < 4; r++) {
            uint32_t x; asm("sub.rn.bf16x2 %0,%1,%2;" : "=r"(x) : "r"(__byte_perm(d2, 0, k ? 0x3232 : 0x1010)), "r"(((const uint32_t*)w)[48 + r]));
            const uint32_t t = hmul2(hmul2(x, x), 0xc120c120u);
            rb[k][r] = pack2(__expf(bf_lo(t)), __expf(bf_hi(t)));
        }
    uint32_t o[4][2];
#pragma unroll
    for (int n = 0; n < 4; n++) {
        float c[4] = {};
        mma_edge(c, rb[0][0], rb[1][0], rb[0][1], rb[1][1], b_frag(w + (n >> 1) * 32, (n & 1) * 2));
        mma_edge(c, rb[0][2], rb[1][2], rb[0][3], rb[1][3], b_frag(w + (n >> 1) * 32 + 16, (n & 1) * 2));
        o[n][0] = pack2(c[0], c[1]); o[n][1] = pack2(c[2], c[3]);
    }
    gp = make_uint4(o[0][0], o[1][0], o[0][1], o[1][1]);
    sp = make_uint4(o[2][0], o[3][0], o[2][1], o[3][1]);
}
__device__ __forceinline__ uint4 edge_finish(const uint16_t* w, uint4 a, uint4 sp, uint4 gp, uint4 mv) {
    float t0[4] = {}, t1[4] = {}, u0[4] = {}, u1[4] = {};
    mma_edge(t0, a.x, a.z, a.y, a.w, b_frag(w + 64, 0));
    mma_edge(t1, a.x, a.z, a.y, a.w, b_frag(w + 64, 2));
    const uint32_t p01 = pack2(t0[0] * bf_lo(sp.x), t0[1] * bf_hi(sp.x)), p23 = pack2(t1[0] * bf_lo(sp.y), t1[1] * bf_hi(sp.y));
    const uint32_t q01 = pack2(t0[2] * bf_lo(sp.z), t0[3] * bf_hi(sp.z)), q23 = pack2(t1[2] * bf_lo(sp.w), t1[3] * bf_hi(sp.w));
    mma_edge(u0, p01, q01, p23, q23, b_frag(w + 80, 0));
    mma_edge(u1, p01, q01, p23, q23, b_frag(w + 80, 2));
    return make_uint4(hadd2(mv.x, hmul2(pack2(u0[0], u0[1]), gp.x)), hadd2(mv.y, hmul2(pack2(u1[0], u1[1]), gp.y)),
                      hadd2(mv.z, hmul2(pack2(u0[2], u0[3]), gp.z)), hadd2(mv.w, hmul2(pack2(u1[2], u1[3]), gp.w)));
}

__device__ __forceinline__ void finish(const Params& p, unsigned char* sm) {
    __syncwarp();
    const int b = blockIdx.x, tid = threadIdx.x;
    const int role = __shfl_sync(0xffffffffu, ((const volatile uint32_t*)(sm + SM_AUX + AUX_MISC))[2], 0);
    const uint16_t* w = (const uint16_t*)(sm + SM_AUX + AUX_W);
    if (role != 3) {
        __syncthreads();
        if (tid == 0) asm volatile("red.release.gpu.global.add.u32 [%0],1;" ::"l"(&g_sync[SY_END]) : "memory");
        __syncwarp();
    }
    constexpr int EP = 3, es = NCTA * 1024;
    static_assert(EP * es * 2 >= E_CAP, "epilogue");
    uint4 sg[2 * EP];
    const int e0 = b * 1024 + tid, np = p.E / 2;
#pragma unroll
    for (int k = 0; k < EP; k++) sg[2 * k].x = __ldg((const uint32_t*)p.dist + min(e0 + k * es, np - 1));
#pragma unroll
    for (int k = 0; k < EP; k++) edge_gates(w, sg[2 * k].x, sg[2 * k], sg[2 * k + 1]);
    uint4 mv[EP];
#pragma unroll
    for (int k = 0; k < EP; k++) mv[k] = __ldg((const uint4*)p.m + min(e0 + k * es, np - 1));
    if (role == 3) {
        const int et = tid - EXPORT_LO * 32;
        if (et >= 0 && et < EXPORT_N * 32) {
            const int q0 = (((const volatile uint32_t*)(sm + SM_AUX + AUX_MISC))[3] & 255) * (SO / 2);
            bar_sync(1, 992);
#pragma unroll 4
            for (int i = et - (q0 & 7); i < (int)SO / 2; i += EXPORT_N * 32) {
                if (i < 0) continue;
                const uint4 v = ((const uint4*)sm)[i];
                asm volatile("red.global.add.noftz.v4.bf16x2 [%0],{%1,%2,%3,%4};" ::"l"((uint4*)g_agg + q0 + i), "r"(v.x), "r"(v.y), "r"(v.z), "r"(v.w) : "memory");
            }
            __syncwarp();
            bar_arrive(2, 1024);
            bar_sync(3, EXPORT_N * 32);
            if (et == 0) asm volatile("red.release.gpu.global.add.u32 [%0],1;" ::"l"(&g_sync[SY_END]) : "memory");
            __syncwarp();
        } else bar_sync(2, 1024);
    }
    uint4* const stash = (uint4*)sm + tid;
#pragma unroll
    for (int k = 0; k < EP; k++) { stash[(3 * k) * 1024] = sg[2 * k]; stash[(3 * k + 1) * 1024] = sg[2 * k + 1]; stash[(3 * k + 2) * 1024] = mv[k]; }
    if (tid == 0) {
        wait_flag(&g_sync[SY_END], NCTA);
        asm volatile("fence.acquire.gpu;" ::: "memory");
    }
    __syncthreads();
    uint4 av[EP];
#pragma unroll
    for (int k = 0; k < EP; k++) av[k] = __ldcg((const uint4*)g_agg + min(e0 + k * es, np - 1));
#pragma unroll
    for (int k = 0; k < EP; k++) {
        const uint4 o = edge_finish(w, av[k], stash[(3 * k) * 1024], stash[(3 * k + 1) * 1024], stash[(3 * k + 2) * 1024]);
        if (e0 + k * es < np) ((uint4*)p.out)[e0 + k * es] = o;
    }
    if (b == 0 && tid < 512) ((uint4*)flags())[tid] = make_uint4(0, 0, 0, 0);
    if (tid == 0) {
        g_info[b] = make_uint2(0, 0);
        if (atomicAdd(&g_sync[SY_EXIT], 1) == NCTA - 1)
            g_sync[SY_ZERO] = g_sync[SY_END] = g_sync[SY_EXIT] = g_sync[SY_WORK] = g_sync[SY_LOG] = g_sync[SY_LOG + 1] = 0;
    }
}

__global__ void __launch_bounds__(1024, 1) main_kernel(const __grid_constant__ Params p) {
    extern __shared__ __align__(128) unsigned char sm[];
    const int b = blockIdx.x, tid = threadIdx.x, warp = tid >> 5;
    if ((uint32_t)__cvta_generic_to_shared(sm) != SB) __trap();
    uint32_t* s_misc = (uint32_t*)(sm + SM_AUX + AUX_MISC);
    if (tid == 0) s_misc[0] = s_misc[4] = s_misc[5] = 0;
    __syncthreads();
    if ((tid & 31) == 0) {
        const int sl = b * 2 + (warp >> 4), j = warp & 15;
        if (warp == 31) s_misc[1] = upper_is_near(g_probe + (b & 127) * 32);
        else if (sl < NSL && j < (sl < KA ? PA : sl < KA + KV ? PV : 1) && (sl < DS * N1 || sl >= KA || j >= IG / 2) &&
                 upper_is_near(g_ring + (sl < KA ? slot_a(sl) : slot_v(sl - KA)) + j * 8192 + 4064))
            atomicOr(&s_misc[0], 1u << warp);
    }
    __syncwarp();
    __syncthreads();
    uint32_t me; asm("mov.u32 %0,%%smid;" : "=r"(me));
    me = 0x8000u | (s_misc[1] << 14) | (me & 0x3fff);
    if (tid == 0) {
        const u64 v = (u64)(s_misc[0] ^ (s_misc[1] ? ~0u : 0u)) | ((u64)me << 32);
        asm volatile("st.release.gpu.global.u64 [%0],%1;" ::"l"(&g_info[b]), "l"(v) : "memory");
    }
    for (int i = tid; i < (SM_AUX + AUX_CLS) / 16; i += 1024) ((uint4*)sm)[i] = make_uint4(0, 0, 0, 0);
    uint16_t* w = (uint16_t*)(sm + SM_AUX + AUX_W);
    if (tid < 160) {
        u64 v = 0; int spins = 0;
        while (tid < NCTA && !(v >> 32)) {
            asm volatile("ld.acquire.gpu.global.u64 %0,[%1];" : "=l"(v) : "l"(&g_info[tid]) : "memory");
            if (++spins > (1 << 22)) __trap();
        }
        __syncwarp();
        if (tid < NCTA) ((uint32_t*)(sm + SM_AUX + AUX_CLS))[tid] = (uint32_t)v;
        const uint32_t o = v >> 32;
        const uint32_t c = __reduce_add_sync(0xffffffffu, tid < NCTA ? 1u << (8 * ((o & 1) | ((o >> 13) & 2))) : 0u);
        const uint32_t r = __popc(__ballot_sync(0xffffffffu, tid < NCTA && ((o ^ me) & 0x4001) == 0 && (o > me || (o == me && tid > b))));
        if ((tid & 31) == 0) { atomicAdd(&s_misc[4], c); atomicAdd(&s_misc[5], r); }
    } else if (tid >= 256 && tid < 256 + 104) {
        const int j = tid - 256;
        w[j] = j < 32 ? p.w_rbf[j] : j < 64 ? p.w_sbf[j - 32] : j < 80 ? p.w_down[j - 64] : j < 96 ? p.w_up[j - 80] : p.centers[j - 96];
    }
    __syncthreads();
    int role, rank;
    {
        constexpr uint32_t quota = (IG | NO << 8) * 0x10001u;
        const uint32_t cnt = s_misc[4], cl = (me & 1) | ((me >> 13) & 2);
        rank = s_misc[5];
        if (__vminu4(cnt, quota) != quota) {
            role = b < N2 ? 2 : b < N2 + N3 ? 3 : 1;
            const int r = role == 2 ? b : b - N2;
            rank = role == 1 ? b - N2 - N3 : (r >> 1) | ((r & 1) << 8);
        } else if (rank < ((me & 1) ? NO : IG)) {
            role = 2 + (me & 1);
            rank |= (cl >> 1) << 8;
        } else {
            role = 1;
            rank += __dp4a((cnt - quota) & ((1u << (8 * cl)) - 1), 0x01010101u, 0u) - ((me & 1) ? NO : IG);
        }
        role = __shfl_sync(0xffffffffu, role, 0); rank = __shfl_sync(0xffffffffu, rank, 0);
        if (tid == 0) { s_misc[2] = role; s_misc[3] = rank; }
    }
    if (role == 1) stage1(p, sm, rank);
    else if (role == 2) stage2(p, sm, rank >> 8, rank & 255);
    else stage3(p, sm, rank >> 8, rank & 255);
    finish(p, sm);
}

__global__ void generic_scatter(const __grid_constant__ Params p) {
    const float f = bf_lo(p.freq[0]);
    for (int t = blockIdx.x * blockDim.x + threadIdx.x; t < p.T; t += gridDim.x * blockDim.x) {
        const uint2 v = __ldg(p.m + p.idx_in[t]);
        const uint32_t c2 = dup_bf16(cos_any(rbf16(f * bf_lo(p.angle[t]))));
        asm volatile("red.global.add.noftz.v2.bf16x2 [%0],{%1,%2};" ::"l"(p.out + p.idx_out[t]), "r"(hmul2(v.x, c2)), "r"(hmul2(v.y, c2)) : "memory");
    }
}
__global__ void __launch_bounds__(256) generic_finish(const __grid_constant__ Params p) {
    __shared__ __align__(16) uint16_t w[104];
    const int j = threadIdx.x, e = blockIdx.x * blockDim.x + j, ec = min(e, p.E - 1);
    if (j < 104) w[j] = j < 32 ? p.w_rbf[j] : j < 64 ? p.w_sbf[j - 32] : j < 80 ? p.w_down[j - 64] : j < 96 ? p.w_up[j - 80] : p.centers[j - 96];
    const uint2 a = p.out[ec], mv = p.m[ec];
    __syncthreads();
    uint4 s0, s1;
    edge_gates(w, p.dist[ec] * 0x10001u, s0, s1);
    const uint4 o = edge_finish(w, make_uint4(a.x, a.y, a.x, a.y), s0, s1, make_uint4(mv.x, mv.y, mv.x, mv.y));
    if (e < p.E) p.out[e] = make_uint2(o.x, o.y);
}

extern "C" void kernel_launch(void* const* d_in, const int* in_sizes, int n_in, void* d_out, int out_size) {
    static int nsm = 0;
    if (!nsm) {
        int dev = 0;
        cudaGetDevice(&dev);
        cudaDeviceGetAttribute(&nsm, cudaDevAttrMultiProcessorCount, dev);
        cudaFuncSetAttribute(main_kernel, cudaFuncAttributeMaxDynamicSharedMemorySize, SMEM_BYTES);
    }
    Params p;
    p.m = (const uint2*)d_in[0]; p.idx_in = (const int*)d_in[1]; p.idx_out = (const int*)d_in[2];
    p.angle = (const uint16_t*)d_in[4]; p.freq = (const uint16_t*)d_in[6];
    p.dist = (const uint16_t*)d_in[3]; p.centers = (const uint16_t*)d_in[5]; p.w_rbf = (const uint16_t*)d_in[7];
    p.w_sbf = (const uint16_t*)d_in[8]; p.w_down = (const uint16_t*)d_in[9]; p.w_up = (const uint16_t*)d_in[10];
    p.out = (uint2*)d_out;
    p.E = in_sizes[3]; p.T = in_sizes[1];
    p.zero = 0;
    p.pairs = p.T / (2 * STEP); p.units = p.pairs + (NR / 2 + 1) * N1;
    bool fast = nsm >= NCTA && p.E <= E_CAP && p.E >= 8 && p.E % 2 == 0 && p.pairs >= 2 * N1 && p.units < 0xff00;
    static cudaTextureObject_t tex[3];
    static const void* tex_ptr[3];
    static int tex_n[3];
    for (int k = 0; k < 3 && fast; k++) {
        void* ptr = d_in[k == 2 ? 4 : 1 + k];
        if (tex_ptr[k] == ptr && tex_n[k] == p.T) continue;
        cudaResourceDesc rd = {};
        rd.resType = cudaResourceTypeLinear;
        rd.res.linear.devPtr = ptr;
        rd.res.linear.desc = k == 2 ? cudaCreateChannelDesc<uint2>() : cudaCreateChannelDesc<uint4>();
        rd.res.linear.sizeInBytes = (size_t)(p.T / 4) * (k == 2 ? 8 : 16);
        cudaTextureDesc td = {};
        td.readMode = cudaReadModeElementType;
        if (cudaCreateTextureObject(&tex[k], &rd, &td, nullptr) == cudaSuccess) { tex_ptr[k] = ptr; tex_n[k] = p.T; }
        else { cudaGetLastError(); tex_ptr[k] = nullptr; fast = false; }
    }
    p.tin = tex[0]; p.tout = tex[1]; p.tang = tex[2];
    if (fast) {
        void* args[] = {&p};
        if (cudaLaunchCooperativeKernel((const void*)main_kernel, dim3(NCTA), dim3(1024), args, SMEM_BYTES, cudaStreamPerThread) == cudaSuccess) return;
        cudaGetLastError();
    }
    cudaMemsetAsync(d_out, 0, (size_t)p.E * 8, cudaStreamPerThread);
    generic_scatter<<<nsm * 8, 256, 0, cudaStreamPerThread>>>(p);
    generic_finish<<<(p.E + 255) / 256, 256, 0, cudaStreamPerThread>>>(p);
}
```
